```python
import torch

def _softmax(x, axis=-1):
    return torch.softmax(x, dim=axis)

def _gelu(x):
    return torch.nn.functional.gelu(x, approximate='tanh')

def _silu(x):
    return torch.nn.functional.silu(x)

def _sigmoid(x):
    return torch.sigmoid(x)

def _layernorm(x, axis=-1, eps=1e-05):
    m = x.mean(dim=axis, keepdim=True)
    v = x.var(dim=axis, keepdim=True, unbiased=False)
    return (x - m) / torch.sqrt(v + eps)

def _scatter_add(tgt, idx, src, axis=0):
    return tgt.clone().index_add_(axis, idx, src)

def _segment_sum(src, seg, n):
    out = torch.zeros((n,) + src.shape[1:], dtype=src.dtype)
    return out.index_add_(0, seg, src)

def _pad(x, pw):
    flat = tuple((v for pair in reversed(pw) for v in pair))
    return torch.nn.functional.pad(x, flat)
kernel_name = 'adaLN_cond__memory_aug_recurrent_mem_tr__dense_activation_silu__prompt'

def setup_inputs():

    _w = lambda a: (lambda t: t.to(torch.bfloat16) if t.is_floating_point() else t)(torch.as_tensor(a))

    def _A_setup():
        B, S, Dm = (1, 2048, 640)
        H, Dh = (32, 192)
        M, seg = (8, 32)
        seg = min(seg, S)
        S = S // seg * seg
        return {'x': _w((lambda *s: torch.randn(*s, dtype=torch.bfloat16) * 0.05)(B, S, Dm)), 'mem0': _w((lambda *s: torch.randn(*s, dtype=torch.bfloat16) * 0.8)(B, M, Dm)), 'Wq': _w((lambda *s: torch.randn(*s, dtype=torch.bfloat16) * 0.8)(Dm, H, Dh) * Dm ** (-0.5)), 'Wk': _w((lambda *s: torch.randn(*s, dtype=torch.bfloat16) * 0.8)(Dm, H, Dh) * Dm ** (-0.5)), 'Wv': _w((lambda *s: torch.randn(*s, dtype=torch.bfloat16) * 0.8)(Dm, H, Dh) * Dm ** (-0.5)), 'Wo': _w((lambda *s: torch.randn(*s, dtype=torch.bfloat16) * 0.8)(H, Dh, Dm) * (H * Dh) ** (-0.5)), 'seg_len': seg}
    _A_in = _A_setup()

    def _B_setup():
        B, S, D, F = (1, 2048, 640, 1536)
        return {'x': _w((lambda *s: torch.randn(*s, dtype=torch.bfloat16) * 0.05)(B, S, D)), 'w1': _w((lambda *s: torch.randn(*s, dtype=torch.bfloat16) * 0.8)(D, F) * D ** (-0.5)), 'w2': _w((lambda *s: torch.randn(*s, dtype=torch.bfloat16) * 0.2)(F, D) * F ** (-0.5))}
    _B_in = _B_setup()
    return {'A_x': _A_in['x'], 'A_mem0': _A_in['mem0'], 'A_Wq': _A_in['Wq'], 'A_Wk': _A_in['Wk'], 'A_Wv': _A_in['Wv'], 'A_Wo': _A_in['Wo'], 'A_seg_len': _A_in['seg_len'], 'B_x': _B_in['x'], 'B_w1': _B_in['w1'], 'B_w2': _B_in['w2'], 'c': _w((lambda *s: torch.randn(*s, dtype=torch.bfloat16) * 0.1)(1, 640) * 8.0), 'w_mod': _w((lambda *s: torch.randn(*s, dtype=torch.bfloat16) * 0.1)(640, 6 * 640) * 640 ** (-0.5) * 8.0)}

def reference(A_x, A_mem0, A_Wq, A_Wk, A_Wv, A_Wo, A_seg_len, B_x, B_w1, B_w2, c, w_mod):

    def _A_ref(x, mem0, Wq, Wk, Wv, Wo, seg_len):
        B, S, Dm = x.shape
        H, Dh = (Wq.shape[1], Wq.shape[2])
        M = mem0.shape[1]
        scale = Dh ** (-0.5)
        n_seg = S // seg_len
        L = M + seg_len
        idx = torch.arange(L)
        mask = (idx[:, None] < M) | (idx[:, None] >= idx[None, :])
        mem = mem0
        outs = []
        for s in range(n_seg):
            xs = x[:, s * seg_len:(s + 1) * seg_len, :].clone()
            h = torch.concatenate([mem, xs], axis=1)
            q = torch.einsum('btd,dhe->bhte', h, Wq)
            k = torch.einsum('btd,dhe->bhte', h, Wk)
            v = torch.einsum('btd,dhe->bhte', h, Wv)
            scores = torch.einsum('bhqe,bhke->bhqk', q, k) * scale
            scores = torch.where(mask[None, None], scores, -1000000000.0)
            p = _softmax(scores, axis=-1)
            o = torch.einsum('bhqk,bhke->bhqe', p, v)
            o = torch.einsum('bhte,hed->btd', o, Wo)
            mem = o[:, :M, :].clone()
            outs.append(o[:, M:, :])
        return torch.concatenate(outs, axis=1)

    def _B_ref(x, w1, w2):
        h = torch.einsum('bsd,df->bsf', x, w1)
        h = _silu(h)
        out = torch.einsum('bsf,fd->bsd', h, w2)
        return out
    x = A_x
    mod = (_silu(c) @ w_mod).reshape(c.shape[0], 6, 1, -1)
    sa, ca, ga, sb, cb, gb = (mod[:, 0].clone(), mod[:, 1].clone(), mod[:, 2].clone(), mod[:, 3].clone(), mod[:, 4].clone(), mod[:, 5].clone())
    h = _layernorm(x, axis=-1) * (1 + ca) + sa
    x = x + ga * _A_ref(h, A_mem0, A_Wq, A_Wk, A_Wv, A_Wo, A_seg_len)
    h = _layernorm(x, axis=-1) * (1 + cb) + sb
    x = x + gb * _B_ref(h, B_w1, B_w2)
    return x
```

```cpp
#include <cuda_runtime.h>
#include <cuda_bf16.h>
#include <cuda.h>
#include <stdint.h>

typedef __nv_bfloat16 bf16;

constexpr int S_TOK = 2048, DM = 640, NH = 32, DH = 192, HD = NH * DH, NMEM = 8, SEG = 32, NSEG = 64, FF = 1536;
constexpr uint32_t SENT = 0xFFFFFFFFu;
constexpr int NWORD = DM * NMEM / 2;

__device__ float g_mod[6 * DM];
__device__ __align__(1024) bf16 g_h[S_TOK * DM];
__device__ __align__(1024) bf16 g_q[S_TOK * HD];
__device__ __align__(1024) bf16 g_k[S_TOK * HD];
__device__ __align__(1024) bf16 g_v[S_TOK * HD];
__device__ __align__(1024) bf16 g_km[NSEG * NH * NMEM * DH];
__device__ __align__(1024) bf16 g_vm[NSEG * NH * NMEM * DH];
__device__ __align__(1024) bf16 g_o[S_TOK * HD];
__device__ __align__(1024) uint2 g_x1f[S_TOK * DM / 4];
__device__ __align__(1024) float4 g_acc[S_TOK * DM / 4];
__device__ __align__(1024) bf16 g_h2[S_TOK * DM];
__device__ __align__(1024) bf16 g_f[S_TOK * FF];
__device__ __align__(8192) uint32_t g_part[2 * 80 * 3 * 2048];
__device__ __align__(8192) uint32_t g_bc[4 * 3 * 2048];
__device__ uint32_t g_tab[96];
enum { CN_SEG = 0, CN_Q = 64, CN_ATT = 80, CN_WO = 96, CN_LN = 112, CN_F1 = 128, CN_F2 = 144, CN_Z = 160, CN_CLAIM = 192, CN_QH = 240, CN_MOD = 241, CN_H = 242, CN_TOTAL = 256 };
__device__ __align__(128) uint32_t g_cnt[CN_TOTAL];
__device__ __align__(1024) bf16 g_ht[S_TOK * DM];

#define TS(i)
#define TL(idx)
#define TLG(idx)
__device__ __forceinline__ uint32_t smem_u32(const void* p) { return (uint32_t)__cvta_generic_to_shared(p); }
__device__ __forceinline__ uint32_t pack_bf16(float lo, float hi) {
  uint32_t r;
  asm("cvt.rn.bf16x2.f32 %0, %1, %2;" : "=r"(r) : "f"(hi), "f"(lo));
  return r;
}
__device__ __forceinline__ float bf_lo(uint32_t w) { return __uint_as_float(w << 16); }
__device__ __forceinline__ float bf_hi(uint32_t w) { return __uint_as_float(w & 0xFFFF0000u); }
__device__ __forceinline__ float round_bf16(float x) { return __bfloat162float(__float2bfloat16_rn(x)); }

__device__ __forceinline__ void mbar_init(uint32_t bar, uint32_t cnt) {
  asm volatile("mbarrier.init.shared::cta.b64 [%0], %1;" ::"r"(bar), "r"(cnt) : "memory");
}
__device__ __forceinline__ void mbar_expect_tx(uint32_t bar, uint32_t bytes) {
  asm volatile("mbarrier.arrive.expect_tx.shared::cta.b64 _, [%0], %1;" ::"r"(bar), "r"(bytes) : "memory");
}
__device__ __forceinline__ void mbar_arrive(uint32_t bar) {
  asm volatile("mbarrier.arrive.shared::cta.b64 _, [%0];" ::"r"(bar) : "memory");
}
__device__ __forceinline__ bool mbar_try(uint32_t bar, uint32_t parity) {
  uint32_t ok;
  asm volatile(
      "{\n.reg .pred p;\nmbarrier.try_wait.parity.shared::cta.b64 p, [%1], %2;\nselp.u32 %0, 1, 0, p;\n}\n"
      : "=r"(ok)
      : "r"(bar), "r"(parity)
      : "memory");
  return ok != 0;
}
__device__ __forceinline__ bool mbar_try_cl(uint32_t bar, uint32_t parity) {
  uint32_t ok;
  asm volatile(
      "{\n.reg .pred p;\nmbarrier.try_wait.parity.acquire.cluster.shared::cta.b64 p, [%1], %2;\nselp.u32 %0, 1, 0, p;\n}\n"
      : "=r"(ok)
      : "r"(bar), "r"(parity)
      : "memory");
  return ok != 0;
}
struct Spin {
  uint32_t it = 0, t0 = 0;
  __device__ __forceinline__ void tick() {
    if ((++it & 15u) == 0) {
      uint32_t t;
      asm volatile("mov.u32 %0, %%globaltimer_lo;" : "=r"(t));
      if (it == 16u) t0 = t;
      asm volatile("{\n.reg .pred p;\nsetp.gt.u32 p, %0, 1000000000;\n@p trap;\n}" ::"r"(t - t0));
    }
  }
};
__device__ __forceinline__ void mbar_wait(uint32_t bar, uint32_t parity) {
  if (mbar_try(bar, parity)) return;
  Spin sp;
  while (!mbar_try(bar, parity)) sp.tick();
}
__device__ __forceinline__ void mbar_wait_cl(uint32_t bar, uint32_t parity) {
  if (mbar_try_cl(bar, parity)) return;
  Spin sp;
  while (!mbar_try_cl(bar, parity)) sp.tick();
}
__device__ __forceinline__ void fence_proxy_async() { asm volatile("fence.proxy.async.shared::cta;" ::: "memory"); }
__device__ __forceinline__ void fence_mbar_init() { asm volatile("fence.mbarrier_init.release.cluster;" ::: "memory"); }
__device__ __forceinline__ void bar_sync(int id, int n) { asm volatile("bar.sync %0, %1;" ::"r"(id), "r"(n) : "memory"); }
__device__ __forceinline__ void bar_arrive(int id, int n) { asm volatile("bar.arrive %0, %1;" ::"r"(id), "r"(n) : "memory"); }
__device__ __forceinline__ void cluster_sync_all() {
  asm volatile("barrier.cluster.arrive.release.aligned;\nbarrier.cluster.wait.acquire.aligned;" ::: "memory");
}
__device__ __forceinline__ uint32_t cluster_rank() {
  uint32_t r;
  asm volatile("mov.u32 %0, %%cluster_ctarank;" : "=r"(r));
  return r;
}
__device__ __forceinline__ uint32_t mapa(uint32_t addr, uint32_t rank) {
  uint32_t r;
  asm volatile("mapa.shared::cluster.u32 %0, %1, %2;" : "=r"(r) : "r"(addr), "r"(rank));
  return r;
}
__device__ __forceinline__ void st_async_v4(uint32_t addr, uint32_t bar, uint32_t a, uint32_t b, uint32_t c, uint32_t d) {
  asm volatile("st.async.weak.shared::cluster.mbarrier::complete_tx::bytes.v4.b32 [%0], {%2, %3, %4, %5}, [%1];" ::"r"(addr),
               "r"(bar), "r"(a), "r"(b), "r"(c), "r"(d)
               : "memory");
}
__device__ __forceinline__ void st_async_v2(uint32_t addr, uint32_t bar, uint32_t a, uint32_t b) {
  asm volatile("st.async.weak.shared::cluster.mbarrier::complete_tx::bytes.v2.b32 [%0], {%2, %3}, [%1];" ::"r"(addr), "r"(bar),
               "r"(a), "r"(b)
               : "memory");
}
__device__ __forceinline__ void tma_load_2d(uint32_t dst, const CUtensorMap* tm, uint32_t bar, int c0, int c1) {
  asm volatile("cp.async.bulk.tensor.2d.shared::cluster.global.mbarrier::complete_tx::bytes [%0], [%1, {%3, %4}], [%2];" ::"r"(dst),
               "l"((uint64_t)tm), "r"(bar), "r"(c0), "r"(c1)
               : "memory");
}
__device__ __forceinline__ void ldsm_x4(uint32_t (&r)[4], uint32_t addr) {
  asm volatile("ldmatrix.sync.aligned.m8n8.x4.shared.b16 {%0,%1,%2,%3}, [%4];"
               : "=r"(r[0]), "=r"(r[1]), "=r"(r[2]), "=r"(r[3])
               : "r"(addr)
               : "memory");
}
__device__ __forceinline__ void ldsm_x4_t(uint32_t (&r)[4], uint32_t addr) {
  asm volatile("ldmatrix.sync.aligned.m8n8.x4.trans.shared.b16 {%0,%1,%2,%3}, [%4];"
               : "=r"(r[0]), "=r"(r[1]), "=r"(r[2]), "=r"(r[3])
               : "r"(addr)
               : "memory");
}
__device__ __forceinline__ void mma16816(float (&c)[4], const uint32_t (&a)[4], uint32_t b0, uint32_t b1) {
  asm volatile("mma.sync.aligned.m16n8k16.row.col.f32.bf16.bf16.f32 {%0,%1,%2,%3}, {%4,%5,%6,%7}, {%8,%9}, {%0,%1,%2,%3};"
               : "+f"(c[0]), "+f"(c[1]), "+f"(c[2]), "+f"(c[3])
               : "r"(a[0]), "r"(a[1]), "r"(a[2]), "r"(a[3]), "r"(b0), "r"(b1));
}
__device__ __forceinline__ void mma1688(float (&c)[4], uint32_t a0, uint32_t a1, uint32_t b0) {
  asm volatile("mma.sync.aligned.m16n8k8.row.col.f32.bf16.bf16.f32 {%0,%1,%2,%3}, {%4,%5}, {%6}, {%0,%1,%2,%3};"
               : "+f"(c[0]), "+f"(c[1]), "+f"(c[2]), "+f"(c[3])
               : "r"(a0), "r"(a1), "r"(b0));
}
__device__ __forceinline__ void sts32(uint32_t addr, uint32_t v) { asm volatile("st.shared.b32 [%0], %1;" ::"r"(addr), "r"(v) : "memory"); }
__device__ __forceinline__ void sts64(uint32_t addr, uint32_t a, uint32_t b) {
  asm volatile("st.shared.v2.b32 [%0], {%1,%2};" ::"r"(addr), "r"(a), "r"(b) : "memory");
}
__device__ __forceinline__ void sts128(uint32_t addr, uint4 v) {
  asm volatile("st.shared.v4.b32 [%0], {%1,%2,%3,%4};" ::"r"(addr), "r"(v.x), "r"(v.y), "r"(v.z), "r"(v.w) : "memory");
}
__device__ __forceinline__ uint4 lds128(uint32_t addr) {
  uint4 v;
  asm volatile("ld.shared.v4.b32 {%0,%1,%2,%3}, [%4];" : "=r"(v.x), "=r"(v.y), "=r"(v.z), "=r"(v.w) : "r"(addr) : "memory");
  return v;
}
__device__ __forceinline__ uint2 lds64(uint32_t addr) {
  uint2 v;
  asm volatile("ld.shared.v2.b32 {%0,%1}, [%2];" : "=r"(v.x), "=r"(v.y) : "r"(addr) : "memory");
  return v;
}
__device__ __forceinline__ uint32_t lds32(uint32_t addr) {
  uint32_t v;
  asm volatile("ld.shared.b32 %0, [%1];" : "=r"(v) : "r"(addr) : "memory");
  return v;
}
__device__ __forceinline__ uint32_t ld_relaxed32(const uint32_t* p) {
  uint32_t v;
  asm volatile("ld.relaxed.gpu.global.b32 %0, [%1];" : "=r"(v) : "l"(p) : "memory");
  return v;
}
__device__ __forceinline__ uint4 ld_relaxed128(const uint32_t* p) {
  uint4 v;
  asm volatile("ld.relaxed.gpu.global.v4.b32 {%0,%1,%2,%3}, [%4];" : "=r"(v.x), "=r"(v.y), "=r"(v.z), "=r"(v.w) : "l"(p) : "memory");
  return v;
}
__device__ __forceinline__ void st_relaxed32(uint32_t* p, uint32_t v) {
  asm volatile("st.relaxed.gpu.global.b32 [%0], %1;" ::"l"(p), "r"(v) : "memory");
}
__device__ __forceinline__ void st_relaxed64(uint32_t* p, uint32_t a, uint32_t b) {
  asm volatile("st.relaxed.gpu.global.v2.b32 [%0], {%1, %2};" ::"l"(p), "r"(a), "r"(b) : "memory");
}
__device__ __forceinline__ void wgmma_fence() { asm volatile("wgmma.fence.sync.aligned;" ::: "memory"); }
__device__ __forceinline__ void wgmma_commit() { asm volatile("wgmma.commit_group.sync.aligned;" ::: "memory"); }
template <int N>
__device__ __forceinline__ void wgmma_wait() {
  asm volatile("wgmma.wait_group.sync.aligned %0;" ::"n"(N) : "memory");
}
template <int R>
__device__ __forceinline__ void reg_alloc() {
  asm volatile("setmaxnreg.inc.sync.aligned.u32 %0;" ::"n"(R));
}
template <int R>
__device__ __forceinline__ void reg_dealloc() {
  asm volatile("setmaxnreg.dec.sync.aligned.u32 %0;" ::"n"(R));
}
__device__ __forceinline__ uint64_t make_desc(uint32_t addr, uint32_t lbo, uint32_t sbo, uint32_t swz) {
  return (uint64_t)((addr & 0x3FFFF) >> 4) | ((uint64_t)(lbo >> 4) << 16) | ((uint64_t)(sbo >> 4) << 32) | ((uint64_t)swz << 62);
}
template <int N>
__device__ __forceinline__ void fence_regs(float (&d)[N]) {
#pragma unroll
  for (int i = 0; i < N; i++) asm volatile("" : "+f"(d[i])::"memory");
}

template<int TA, int TB> __device__ __forceinline__ void wgmma_ss_n32(float (&d)[16], uint64_t da, uint64_t db, int sc) {
  asm volatile("{\n.reg .pred p;\nsetp.ne.b32 p, %18, 0;\n"
    "wgmma.mma_async.sync.aligned.m64n32k16.f32.bf16.bf16 {%0, %1, %2, %3, %4, %5, %6, %7, %8, %9, %10, %11, %12, %13, %14, %15}, %16, %17, p, 1, 1, %19, %20;\n}\n"
    : "+f"(d[0]), "+f"(d[1]), "+f"(d[2]), "+f"(d[3]), "+f"(d[4]), "+f"(d[5]), "+f"(d[6]), "+f"(d[7]), "+f"(d[8]), "+f"(d[9]), "+f"(d[10]), "+f"(d[11]), "+f"(d[12]), "+f"(d[13]), "+f"(d[14]), "+f"(d[15])
    : "l"(da), "l"(db), "r"(sc), "n"(TA), "n"(TB));
}
template<int TA, int TB> __device__ __forceinline__ void wgmma_ss_n64(float (&d)[32], uint64_t da, uint64_t db, int sc) {
  asm volatile("{\n.reg .pred p;\nsetp.ne.b32 p, %34, 0;\n"
    "wgmma.mma_async.sync.aligned.m64n64k16.f32.bf16.bf16 {%0, %1, %2, %3, %4, %5, %6, %7, %8, %9, %10, %11, %12, %13, %14, %15, %16, %17, %18, %19, %20, %21, %22, %23, %24, %25, %26, %27, %28, %29, %30, %31}, %32, %33, p, 1, 1, %35, %36;\n}\n"
    : "+f"(d[0]), "+f"(d[1]), "+f"(d[2]), "+f"(d[3]), "+f"(d[4]), "+f"(d[5]), "+f"(d[6]), "+f"(d[7]), "+f"(d[8]), "+f"(d[9]), "+f"(d[10]), "+f"(d[11]), "+f"(d[12]), "+f"(d[13]), "+f"(d[14]), "+f"(d[15]), "+f"(d[16]), "+f"(d[17]), "+f"(d[18]), "+f"(d[19]), "+f"(d[20]), "+f"(d[21]), "+f"(d[22]), "+f"(d[23]), "+f"(d[24]), "+f"(d[25]), "+f"(d[26]), "+f"(d[27]), "+f"(d[28]), "+f"(d[29]), "+f"(d[30]), "+f"(d[31])
    : "l"(da), "l"(db), "r"(sc), "n"(TA), "n"(TB));
}
template<int TA, int TB> __device__ __forceinline__ void wgmma_ss_n128(float (&d)[64], uint64_t da, uint64_t db, int sc) {
  asm volatile("{\n.reg .pred p;\nsetp.ne.b32 p, %66, 0;\n"
    "wgmma.mma_async.sync.aligned.m64n128k16.f32.bf16.bf16 {%0, %1, %2, %3, %4, %5, %6, %7, %8, %9, %10, %11, %12, %13, %14, %15, %16, %17, %18, %19, %20, %21, %22, %23, %24, %25, %26, %27, %28, %29, %30, %31, %32, %33, %34, %35, %36, %37, %38, %39, %40, %41, %42, %43, %44, %45, %46, %47, %48, %49, %50, %51, %52, %53, %54, %55, %56, %57, %58, %59, %60, %61, %62, %63}, %64, %65, p, 1, 1, %67, %68;\n}\n"
    : "+f"(d[0]), "+f"(d[1]), "+f"(d[2]), "+f"(d[3]), "+f"(d[4]), "+f"(d[5]), "+f"(d[6]), "+f"(d[7]), "+f"(d[8]), "+f"(d[9]), "+f"(d[10]), "+f"(d[11]), "+f"(d[12]), "+f"(d[13]), "+f"(d[14]), "+f"(d[15]), "+f"(d[16]), "+f"(d[17]), "+f"(d[18]), "+f"(d[19]), "+f"(d[20]), "+f"(d[21]), "+f"(d[22]), "+f"(d[23]), "+f"(d[24]), "+f"(d[25]), "+f"(d[26]), "+f"(d[27]), "+f"(d[28]), "+f"(d[29]), "+f"(d[30]), "+f"(d[31]), "+f"(d[32]), "+f"(d[33]), "+f"(d[34]), "+f"(d[35]), "+f"(d[36]), "+f"(d[37]), "+f"(d[38]), "+f"(d[39]), "+f"(d[40]), "+f"(d[41]), "+f"(d[42]), "+f"(d[43]), "+f"(d[44]), "+f"(d[45]), "+f"(d[46]), "+f"(d[47]), "+f"(d[48]), "+f"(d[49]), "+f"(d[50]), "+f"(d[51]), "+f"(d[52]), "+f"(d[53]), "+f"(d[54]), "+f"(d[55]), "+f"(d[56]), "+f"(d[57]), "+f"(d[58]), "+f"(d[59]), "+f"(d[60]), "+f"(d[61]), "+f"(d[62]), "+f"(d[63])
    : "l"(da), "l"(db), "r"(sc), "n"(TA), "n"(TB));
}
template<int TA, int TB> __device__ __forceinline__ void wgmma_ss_n192(float (&d)[96], uint64_t da, uint64_t db, int sc) {
  asm volatile("{\n.reg .pred p;\nsetp.ne.b32 p, %98, 0;\n"
    "wgmma.mma_async.sync.aligned.m64n192k16.f32.bf16.bf16 {%0, %1, %2, %3, %4, %5, %6, %7, %8, %9, %10, %11, %12, %13, %14, %15, %16, %17, %18, %19, %20, %21, %22, %23, %24, %25, %26, %27, %28, %29, %30, %31, %32, %33, %34, %35, %36, %37, %38, %39, %40, %41, %42, %43, %44, %45, %46, %47, %48, %49, %50, %51, %52, %53, %54, %55, %56, %57, %58, %59, %60, %61, %62, %63, %64, %65, %66, %67, %68, %69, %70, %71, %72, %73, %74, %75, %76, %77, %78, %79, %80, %81, %82, %83, %84, %85, %86, %87, %88, %89, %90, %91, %92, %93, %94, %95}, %96, %97, p, 1, 1, %99, %100;\n}\n"
    : "+f"(d[0]), "+f"(d[1]), "+f"(d[2]), "+f"(d[3]), "+f"(d[4]), "+f"(d[5]), "+f"(d[6]), "+f"(d[7]), "+f"(d[8]), "+f"(d[9]), "+f"(d[10]), "+f"(d[11]), "+f"(d[12]), "+f"(d[13]), "+f"(d[14]), "+f"(d[15]), "+f"(d[16]), "+f"(d[17]), "+f"(d[18]), "+f"(d[19]), "+f"(d[20]), "+f"(d[21]), "+f"(d[22]), "+f"(d[23]), "+f"(d[24]), "+f"(d[25]), "+f"(d[26]), "+f"(d[27]), "+f"(d[28]), "+f"(d[29]), "+f"(d[30]), "+f"(d[31]), "+f"(d[32]), "+f"(d[33]), "+f"(d[34]), "+f"(d[35]), "+f"(d[36]), "+f"(d[37]), "+f"(d[38]), "+f"(d[39]), "+f"(d[40]), "+f"(d[41]), "+f"(d[42]), "+f"(d[43]), "+f"(d[44]), "+f"(d[45]), "+f"(d[46]), "+f"(d[47]), "+f"(d[48]), "+f"(d[49]), "+f"(d[50]), "+f"(d[51]), "+f"(d[52]), "+f"(d[53]), "+f"(d[54]), "+f"(d[55]), "+f"(d[56]), "+f"(d[57]), "+f"(d[58]), "+f"(d[59]), "+f"(d[60]), "+f"(d[61]), "+f"(d[62]), "+f"(d[63]), "+f"(d[64]), "+f"(d[65]), "+f"(d[66]), "+f"(d[67]), "+f"(d[68]), "+f"(d[69]), "+f"(d[70]), "+f"(d[71]), "+f"(d[72]), "+f"(d[73]), "+f"(d[74]), "+f"(d[75]), "+f"(d[76]), "+f"(d[77]), "+f"(d[78]), "+f"(d[79]), "+f"(d[80]), "+f"(d[81]), "+f"(d[82]), "+f"(d[83]), "+f"(d[84]), "+f"(d[85]), "+f"(d[86]), "+f"(d[87]), "+f"(d[88]), "+f"(d[89]), "+f"(d[90]), "+f"(d[91]), "+f"(d[92]), "+f"(d[93]), "+f"(d[94]), "+f"(d[95])
    : "l"(da), "l"(db), "r"(sc), "n"(TA), "n"(TB));
}
template<int TA, int TB> __device__ __forceinline__ void wgmma_ss_n256(float (&d)[128], uint64_t da, uint64_t db, int sc) {
  asm volatile("{\n.reg .pred p;\nsetp.ne.b32 p, %130, 0;\n"
    "wgmma.mma_async.sync.aligned.m64n256k16.f32.bf16.bf16 {%0, %1, %2, %3, %4, %5, %6, %7, %8, %9, %10, %11, %12, %13, %14, %15, %16, %17, %18, %19, %20, %21, %22, %23, %24, %25, %26, %27, %28, %29, %30, %31, %32, %33, %34, %35, %36, %37, %38, %39, %40, %41, %42, %43, %44, %45, %46, %47, %48, %49, %50, %51, %52, %53, %54, %55, %56, %57, %58, %59, %60, %61, %62, %63, %64, %65, %66, %67, %68, %69, %70, %71, %72, %73, %74, %75, %76, %77, %78, %79, %80, %81, %82, %83, %84, %85, %86, %87, %88, %89, %90, %91, %92, %93, %94, %95, %96, %97, %98, %99, %100, %101, %102, %103, %104, %105, %106, %107, %108, %109, %110, %111, %112, %113, %114, %115, %116, %117, %118, %119, %120, %121, %122, %123, %124, %125, %126, %127}, %128, %129, p, 1, 1, %131, %132;\n}\n"
    : "+f"(d[0]), "+f"(d[1]), "+f"(d[2]), "+f"(d[3]), "+f"(d[4]), "+f"(d[5]), "+f"(d[6]), "+f"(d[7]), "+f"(d[8]), "+f"(d[9]), "+f"(d[10]), "+f"(d[11]), "+f"(d[12]), "+f"(d[13]), "+f"(d[14]), "+f"(d[15]), "+f"(d[16]), "+f"(d[17]), "+f"(d[18]), "+f"(d[19]), "+f"(d[20]), "+f"(d[21]), "+f"(d[22]), "+f"(d[23]), "+f"(d[24]), "+f"(d[25]), "+f"(d[26]), "+f"(d[27]), "+f"(d[28]), "+f"(d[29]), "+f"(d[30]), "+f"(d[31]), "+f"(d[32]), "+f"(d[33]), "+f"(d[34]), "+f"(d[35]), "+f"(d[36]), "+f"(d[37]), "+f"(d[38]), "+f"(d[39]), "+f"(d[40]), "+f"(d[41]), "+f"(d[42]), "+f"(d[43]), "+f"(d[44]), "+f"(d[45]), "+f"(d[46]), "+f"(d[47]), "+f"(d[48]), "+f"(d[49]), "+f"(d[50]), "+f"(d[51]), "+f"(d[52]), "+f"(d[53]), "+f"(d[54]), "+f"(d[55]), "+f"(d[56]), "+f"(d[57]), "+f"(d[58]), "+f"(d[59]), "+f"(d[60]), "+f"(d[61]), "+f"(d[62]), "+f"(d[63]), "+f"(d[64]), "+f"(d[65]), "+f"(d[66]), "+f"(d[67]), "+f"(d[68]), "+f"(d[69]), "+f"(d[70]), "+f"(d[71]), "+f"(d[72]), "+f"(d[73]), "+f"(d[74]), "+f"(d[75]), "+f"(d[76]), "+f"(d[77]), "+f"(d[78]), "+f"(d[79]), "+f"(d[80]), "+f"(d[81]), "+f"(d[82]), "+f"(d[83]), "+f"(d[84]), "+f"(d[85]), "+f"(d[86]), "+f"(d[87]), "+f"(d[88]), "+f"(d[89]), "+f"(d[90]), "+f"(d[91]), "+f"(d[92]), "+f"(d[93]), "+f"(d[94]), "+f"(d[95]), "+f"(d[96]), "+f"(d[97]), "+f"(d[98]), "+f"(d[99]), "+f"(d[100]), "+f"(d[101]), "+f"(d[102]), "+f"(d[103]), "+f"(d[104]), "+f"(d[105]), "+f"(d[106]), "+f"(d[107]), "+f"(d[108]), "+f"(d[109]), "+f"(d[110]), "+f"(d[111]), "+f"(d[112]), "+f"(d[113]), "+f"(d[114]), "+f"(d[115]), "+f"(d[116]), "+f"(d[117]), "+f"(d[118]), "+f"(d[119]), "+f"(d[120]), "+f"(d[121]), "+f"(d[122]), "+f"(d[123]), "+f"(d[124]), "+f"(d[125]), "+f"(d[126]), "+f"(d[127])
    : "l"(da), "l"(db), "r"(sc), "n"(TA), "n"(TB));
}

template<int TB> __device__ __forceinline__ void wgmma_rs_n32(float (&d)[16], const uint32_t (&a)[4], uint64_t db, int sc) {
  asm volatile("{\n.reg .pred p;\nsetp.ne.b32 p, %21, 0;\n"
    "wgmma.mma_async.sync.aligned.m64n32k16.f32.bf16.bf16 {%0, %1, %2, %3, %4, %5, %6, %7, %8, %9, %10, %11, %12, %13, %14, %15}, {%16, %17, %18, %19}, %20, p, 1, 1, %22;\n}\n"
    : "+f"(d[0]), "+f"(d[1]), "+f"(d[2]), "+f"(d[3]), "+f"(d[4]), "+f"(d[5]), "+f"(d[6]), "+f"(d[7]), "+f"(d[8]), "+f"(d[9]), "+f"(d[10]), "+f"(d[11]), "+f"(d[12]), "+f"(d[13]), "+f"(d[14]), "+f"(d[15])
    : "r"(a[0]), "r"(a[1]), "r"(a[2]), "r"(a[3]), "l"(db), "r"(sc), "n"(TB));
}

__global__ __cluster_dims__(2, 1, 1) __launch_bounds__(640) void k_init(const bf16* __restrict__ mem0, const bf16* __restrict__ cvec, const bf16* __restrict__ wmod) {
  __shared__ float red[32][161];
  __shared__ float sc[DM];
  asm volatile("griddepcontrol.launch_dependents;" ::: "memory");
  TS(0);
  const int t = threadIdx.x, gt = blockIdx.x * 640 + t, nthr = gridDim.x * 640;
  const int cg = t % 20, rg = t / 20;
  const float cf = __bfloat162float(cvec[t]);
  uint4 wv[20];
#pragma unroll
  for (int i = 0; i < 20; i++) {
    wv[i] = __ldg(reinterpret_cast<const uint4*>(wmod + (size_t)(rg + i * 32) * (6 * DM) + blockIdx.x * 160 + cg * 8));
  }
  const uint4 s4 = make_uint4(SENT, SENT, SENT, SENT);
  for (int i = gt; i < 3 * 3 * 2048 / 4; i += nthr) reinterpret_cast<uint4*>(g_bc + 3 * 2048)[i] = s4;
  if (gt < 96) g_tab[gt] = 0;
  if (gt < CN_TOTAL) {
    const int c = gt - CN_CLAIM;
    g_cnt[gt] = c == 35 ? 0x10101010u : c == 19 ? 0x3C3C0000u : c == 15 ? 0x08080800u : c == 11 ? 0x18181800u : c == 7 ? 0x0A0A0A00u : 0u;
  }
  for (int i = gt; i < NWORD; i += nthr) {
    int d = i >> 2, tp = i & 3;
    uint32_t lo = __bfloat16_as_ushort(mem0[(2 * tp) * DM + d]);
    uint32_t hi = __bfloat16_as_ushort(mem0[(2 * tp + 1) * DM + d]);
    uint32_t w = lo | (hi << 16);
    if (w == SENT) w = 0x7FFF7FFFu;
    g_bc[(i >> 10) * 2048 + (i & 1023)] = w;
    g_bc[(i >> 10) * 2048 + 1024 + (i & 1023)] = w;
  }
  sc[t] = round_bf16(cf / (1.f + __expf(-cf)));
  __syncthreads();
  float acc[8];
#pragma unroll
  for (int j = 0; j < 8; j++) acc[j] = 0.f;
#pragma unroll
  for (int i = 0; i < 20; i++) {
    const float sv = sc[rg + i * 32];
    acc[0] += sv * bf_lo(wv[i].x); acc[1] += sv * bf_hi(wv[i].x); acc[2] += sv * bf_lo(wv[i].y); acc[3] += sv * bf_hi(wv[i].y);
    acc[4] += sv * bf_lo(wv[i].z); acc[5] += sv * bf_hi(wv[i].z); acc[6] += sv * bf_lo(wv[i].w); acc[7] += sv * bf_hi(wv[i].w);
  }
#pragma unroll
  for (int j = 0; j < 8; j++) red[rg][cg * 8 + j] = acc[j];
  __syncthreads();
  if (t < 160) {
    float sum = 0.f;
#pragma unroll 8
    for (int r = 0; r < 32; r++) sum += red[r][t];
    g_mod[blockIdx.x * 160 + t] = round_bf16(sum);
  }
}
__device__ __forceinline__ uint32_t ld_acq(const uint32_t* p) {
  uint32_t v;
  asm volatile("ld.acquire.gpu.global.b32 %0, [%1];" : "=r"(v) : "l"(p) : "memory");
  return v;
}
__device__ __forceinline__ void red_release(uint32_t* p) { asm volatile("red.release.gpu.global.add.u32 [%0], 1;" ::"l"(p) : "memory"); }
__device__ __forceinline__ void wait_cnt(const uint32_t* p, uint32_t n) {
  Spin sp;
  while (ld_acq(p) < n) sp.tick();
}

constexpr int R_V = 0;
constexpr int R_H = 81920;
constexpr int R_MEM = R_H + 40960;
constexpr int R_KX = R_MEM + 10240;
constexpr int R_VX = R_KX + 4096;
constexpr int R_XS = R_VX + 4096;
constexpr int R_QS = R_XS + 8192;
constexpr int R_KS = R_QS + 2048;
constexpr int R_SB = R_KS + 2048;
constexpr int R_VE = R_SB + 4608;
constexpr int R_OT = R_VE + 2048;
constexpr int R_VM = R_OT + 1024;
constexpr int R_KM = R_VM + 1024;
constexpr int R_WO = 163840;
constexpr int R_BAR = R_WO + 65536;
constexpr int R_SMEM = R_BAR + 256;
constexpr int R_WOSTG = R_KX;
static_assert(R_KM + 1024 <= R_WO, "layout");
static_assert(R_SMEM <= 232448, "smem");
enum { RB_W0 = 0, RB_W1 = 1, RB_S = 2, RB_H = 4, RB_W2 = 5 };
enum { NB_MEM = 1, NB_QK = 2, NB_O = 3, NB_INIT = 4, NB_X1 = 5, NB_X2 = 6, NB_G1 = 7, NB_V = 8, NB_P = 9, NB_R = 10 };
#define VS 36
#define KFIRST 1
#define RPOS 2
#define FLOOD 1
#define PFPOS 0
#define VJ 10
#define PD0 650
#define PD1 500
#define PD2 2200
#define PD3 0
#define NCAL 6
#define DK 0
#define DV 0
template <int D>
__device__ __forceinline__ void delay() {
  if (D > 0) {
    uint32_t t0, t1;
    asm volatile("mov.u32 %0, %%clock;" : "=r"(t0)::"memory");
    do { asm volatile("mov.u32 %0, %%clock;" : "=r"(t1)::"memory"); } while (t1 - t0 < (uint32_t)D);
  }
}
__device__ __forceinline__ void poll128(uint4& v, const uint32_t* p) {
  asm volatile(
      "{\n.reg .pred p;\nsetp.eq.u32 p, %0, 0xFFFFFFFF;\nsetp.eq.or.u32 p, %1, 0xFFFFFFFF, p;\nsetp.eq.or.u32 p, %2, 0xFFFFFFFF, p;\n"
      "setp.eq.or.u32 p, %3, 0xFFFFFFFF, p;\n@p ld.relaxed.gpu.global.v4.b32 {%0,%1,%2,%3}, [%4];\n}\n"
      : "+r"(v.x), "+r"(v.y), "+r"(v.z), "+r"(v.w)
      : "l"(p)
      : "memory");
}
__device__ __forceinline__ void poll128_if(uint4& v, const uint32_t* p, uint32_t bad) {
  asm volatile("{\n.reg .pred p;\nsetp.ne.u32 p, %5, 0;\n@p ld.relaxed.gpu.global.v4.b32 {%0,%1,%2,%3}, [%4];\n}\n"
               : "+r"(v.x), "+r"(v.y), "+r"(v.z), "+r"(v.w)
               : "l"(p), "r"(bad)
               : "memory");
}
template <int OFF>
__device__ __forceinline__ void st_half(uint32_t* p, uint32_t bit, uint32_t v) {
  asm volatile("{\n.reg .pred p;\nsetp.ne.u32 p, %1, 0;\n@p st.relaxed.gpu.global.b32 [%0+%3], %2;\n@!p st.relaxed.gpu.global.b32 [%0+%4], %2;\n}\n" ::"l"(p),
               "r"(bit), "r"(v), "n"(OFF + 4096), "n"(OFF)
               : "memory");
}
__device__ __forceinline__ uint32_t opaque(uint32_t x) {
  asm volatile("" : "+r"(x));
  return x;
}
__device__ __forceinline__ float ex2(float x) {
  float y;
  asm("ex2.approx.ftz.f32 %0, %1;" : "=f"(y) : "f"(x));
  return y;
}
__device__ __forceinline__ void bulk_s2g(void* dst, uint32_t src, uint32_t bytes) {
  asm volatile("cp.async.bulk.global.shared::cta.bulk_group [%0], [%1], %2;" ::"l"(dst), "r"(src), "r"(bytes) : "memory");
}
__device__ __forceinline__ void bulk_g2s(uint32_t dst, const void* src, uint32_t bytes, uint32_t bar) {
  asm volatile("cp.async.bulk.shared::cluster.global.mbarrier::complete_tx::bytes [%0], [%1], %2, [%3];" ::"r"(dst), "l"(src), "r"(bytes),
               "r"(bar)
               : "memory");
}
__device__ __forceinline__ uint32_t near_half(uint32_t* blk) {
  uint32_t best[2] = {0xFFFFFFFFu, 0xFFFFFFFFu};
#pragma unroll 1
  for (int r = 0; r < NCAL; r++) {
    uint32_t t0, t1, v;
    asm volatile("mov.u32 %0, %%clock;" : "=r"(t0)::"memory");
    asm volatile("atom.relaxed.gpu.global.add.u32 %0, [%1], 0;" : "=r"(v) : "l"(blk + (r & 1) * 1024 + (blockIdx.x & 31) * 32) : "memory");
    asm volatile("{\n.reg .u32 t;\nmov.u32 t, %%clock;\nand.b32 %0, %1, 0;\nadd.u32 %0, %0, t;\n}" : "=r"(t1) : "r"(v) : "memory");
    asm volatile("mov.u32 %0, %%clock;" : "+r"(t1)::"memory");
    if (r & 1) best[1] = min(best[1], t1 - t0); else best[0] = min(best[0], t1 - t0);
  }
  return best[1] < best[0];
}
__device__ __forceinline__ void tma_prefetch_2d(const CUtensorMap* tm, int c0, int c1) {
  asm volatile("cp.async.bulk.prefetch.tensor.2d.L2.global [%0, {%1, %2}];" ::"l"((uint64_t)tm), "r"(c0), "r"(c1) : "memory");
}
__device__ __forceinline__ void bulk_commit() { asm volatile("cp.async.bulk.commit_group;" ::: "memory"); }
__device__ __forceinline__ void bulk_wait_read0() { asm volatile("cp.async.bulk.wait_group.read 0;" ::: "memory"); }
__device__ __forceinline__ void bulk_wait0() { asm volatile("cp.async.bulk.wait_group 0;" ::: "memory"); }
template <int VSW, int N>
__device__ __forceinline__ void store_xt(uint32_t tile, const float (&d)[N], int w, int lane) {
  const int r = w * 16 + (lane >> 2);
  const uint32_t base = tile + r * 64 + (lane & 3) * 4;
  const int sw = ((r >> 1) + VSW * (r >> 3)) & 3, sw2 = (sw + VSW) & 3;
#pragma unroll
  for (int j = 0; j < 4; j++) {
    sts32(base + ((j ^ sw) * 16), pack_bf16(d[j * 4 + 0], d[j * 4 + 1]));
    sts32(base + 512 + ((j ^ sw2) * 16), pack_bf16(d[j * 4 + 2], d[j * 4 + 3]));
  }
}
__device__ __forceinline__ void stage_km(uint32_t sb, int lane) {
#pragma unroll
  for (int i = 0; i < 2; i++) {
    const uint4 a = lds128(sb + R_KS + (i * 32 + lane) * 16), b = lds128(sb + R_KS + 1024 + (i * 32 + lane) * 16);
    uint4 o;
    o.x = pack_bf16(bf_lo(a.x) + bf_lo(b.x), bf_hi(a.x) + bf_hi(b.x));
    o.y = pack_bf16(bf_lo(a.y) + bf_lo(b.y), bf_hi(a.y) + bf_hi(b.y));
    o.z = pack_bf16(bf_lo(a.z) + bf_lo(b.z), bf_hi(a.z) + bf_hi(b.z));
    o.w = pack_bf16(bf_lo(a.w) + bf_lo(b.w), bf_hi(a.w) + bf_hi(b.w));
    sts128(sb + R_KM + (i * 32 + lane) * 16, o);
  }
  fence_proxy_async();
}
__device__ __forceinline__ void seg_done(int s) {
  bulk_wait0();
  asm volatile("red.relaxed.gpu.global.add.u32 [%0], 1;" ::"l"(g_cnt + CN_SEG + s) : "memory");
}
__device__ __forceinline__ constexpr int koff(int j) { return (j >> 2) * 16384 + (j & 3) * 2048; }

#define VMODE 1
constexpr int XK1 = 20, XK2 = 40;
__global__ __cluster_dims__(3, 1, 1) __launch_bounds__(384, 1) void k_rec(
    const __grid_constant__ CUtensorMap tmWq, const __grid_constant__ CUtensorMap tmWk, const __grid_constant__ CUtensorMap tmWv,
    const __grid_constant__ CUtensorMap tmWo, const bf16* __restrict__ x, const bf16* pWv, const bf16* pWo) {
  extern __shared__ __align__(1024) uint8_t smem_raw[];
  const uint32_t sb = smem_u32(smem_raw);
  const int tid = threadIdx.x, lane = tid & 31;
  const int warp = __shfl_sync(0xffffffffu, tid >> 5, 0);
  const int rank = cluster_rank();
  const int cta = blockIdx.x;
  const int li = lane >> 3, lr = lane & 7;
  const uint32_t bar = sb + R_BAR;
  TS(2);
  if (tid == 0) {
    if (sb & 1023) __trap();
    mbar_init(bar + RB_W0 * 8, 1);
    mbar_init(bar + RB_W1 * 8, 1);
    mbar_init(bar + RB_W2 * 8, 1);
    mbar_init(bar + RB_S * 8, 1);
    mbar_init(bar + RB_H * 8, 1);
    sts32(sb + R_BAR + 128, 0);
    fence_mbar_init();
    mbar_expect_tx(bar + RB_S * 8, 4608);
  }
  {
    uint2(*tt)[DM / 4] = reinterpret_cast<uint2(*)[DM / 4]>(smem_raw + R_WO);
#define W0LOAD                                                                         \
  {                                                                                    \
    mbar_expect_tx(bar + RB_W0 * 8, 2 * 81920);                                        \
    for (int i = 0; i < 4; i++) {                                                      \
      tma_load_2d(sb + R_V + i * 20480, &tmWq, bar + RB_W0 * 8, cta * 64, i * 160);    \
      tma_load_2d(sb + R_H + i * 20480, &tmWk, bar + RB_W0 * 8, cta * 64, i * 160);    \
    }                                                                                  \
  }
    float v[2][20], mean[2], rstd[2];
    {
      uint2 xw[2][5];
#pragma unroll
      for (int r = 0; r < 2; r++) {
        const uint2* xr = reinterpret_cast<const uint2*>(x + (size_t)min(cta * 24 + r * 12 + warp, S_TOK - 1) * DM);
#pragma unroll
        for (int i = 0; i < 5; i++) xw[r][i] = __ldg(xr + i * 32 + lane);
      }
      __syncthreads();
      if (FLOOD == 0 && tid == 352) W0LOAD;
      if (lane == 0) {
        uint32_t m = near_half(g_bc + warp * 2048) << warp;
        if (FLOOD == 1 && tid == 352) W0LOAD;
        if (warp < 6 && cta < 80) m |= near_half(g_part + (size_t)(((warp / 3) * 80 + cta) * 3 + warp % 3) * 2048) << (16 + warp);
        if (FLOOD == 2 && tid == 0) W0LOAD;
        atomicOr(reinterpret_cast<uint32_t*>(smem_raw + R_BAR + 128), m);
      }
      __syncwarp();
      TS(1);
#pragma unroll
      for (int r = 0; r < 2; r++)
#pragma unroll
        for (int i = 0; i < 5; i++) {
          v[r][i * 4 + 0] = bf_lo(xw[r][i].x); v[r][i * 4 + 1] = bf_hi(xw[r][i].x);
          v[r][i * 4 + 2] = bf_lo(xw[r][i].y); v[r][i * 4 + 3] = bf_hi(xw[r][i].y);
        }
    }
    if (warp == 11 && lane < 8) {
      const bf16* pw = lane < 4 ? pWv : pWo;
      asm volatile("cp.async.bulk.prefetch.L2.global [%0], 20480;" ::"l"(pw + (size_t)(cta * 4 + (lane & 3)) * 10240) : "memory");
    }
#pragma unroll
    for (int r = 0; r < 2; r++) {
      float sm = 0.f;
#pragma unroll
      for (int i = 0; i < 20; i++) sm += v[r][i];
#pragma unroll
      for (int o = 16; o; o >>= 1) sm += __shfl_xor_sync(0xffffffffu, sm, o);
      mean[r] = sm * (1.f / DM);
      float q = 0.f;
#pragma unroll
      for (int i = 0; i < 20; i++) { const float d = v[r][i] - mean[r]; q += d * d; }
#pragma unroll
      for (int o = 16; o; o >>= 1) q += __shfl_xor_sync(0xffffffffu, q, o);
      rstd[r] = rsqrtf(q * (1.f / DM) + 1e-5f);
    }
    TS(9);
    asm volatile("griddepcontrol.wait;" ::: "memory");
    TS(10);
    cluster_sync_all();
    asm volatile("griddepcontrol.launch_dependents;" ::: "memory");
    TS(3);
    const uint32_t nm = lds32(sb + R_BAR + 128);
    if (cta < 80) {
#pragma unroll
      for (int i = 0; i < 4; i++) {
        const int e = i * 384 + tid, b = e >> 8;
        reinterpret_cast<uint4*>(g_part)[(size_t)(((b / 3) * 80 + cta) * 3 + b % 3) * 512 + ((nm >> (16 + b)) & 1) * 256 + (e & 255)] = make_uint4(SENT, SENT, SENT, SENT);
      }
    }
#pragma unroll
    for (int i = 0; i < 5; i++) {
      const int c0 = (i * 32 + lane) * 4;
      const float4 sc = __ldcg(reinterpret_cast<const float4*>(g_mod + DM + c0)), sh = __ldcg(reinterpret_cast<const float4*>(g_mod + c0));
#pragma unroll
      for (int r = 0; r < 2; r++) {
        const uint2 o = make_uint2(pack_bf16((v[r][i * 4 + 0] - mean[r]) * rstd[r] * (1.f + sc.x) + sh.x, (v[r][i * 4 + 1] - mean[r]) * rstd[r] * (1.f + sc.y) + sh.y),
                                   pack_bf16((v[r][i * 4 + 2] - mean[r]) * rstd[r] * (1.f + sc.z) + sh.z, (v[r][i * 4 + 3] - mean[r]) * rstd[r] * (1.f + sc.w) + sh.w));
        const int row = cta * 24 + r * 12 + warp;
        if (row < S_TOK) reinterpret_cast<uint2*>(g_h + (size_t)row * DM)[i * 32 + lane] = o;
        tt[r * 12 + warp][i * 32 + lane] = o;
      }
    }
    __syncthreads();
    TS(13);
    for (int e = tid; e < 3 * (DM / 2); e += 384) {
      const int gq = e / (DM / 2), c = e % (DM / 2);
      if (cta * 3 + gq < S_TOK / 8) {
        uint32_t r[8];
#pragma unroll
        for (int j = 0; j < 8; j++) r[j] = reinterpret_cast<const uint32_t*>(tt[gq * 8 + j])[c];
        uint4* dst = reinterpret_cast<uint4*>(g_ht) + (size_t)(cta * 3 + gq) * DM + c * 2;
        dst[0] = make_uint4(__byte_perm(r[0], r[1], 0x5410), __byte_perm(r[2], r[3], 0x5410), __byte_perm(r[4], r[5], 0x5410), __byte_perm(r[6], r[7], 0x5410));
        dst[1] = make_uint4(__byte_perm(r[0], r[1], 0x7632), __byte_perm(r[2], r[3], 0x7632), __byte_perm(r[4], r[5], 0x7632), __byte_perm(r[6], r[7], 0x7632));
      }
    }
    fence_proxy_async();
    __syncthreads();
    TS(14);
  }

  if (warp < 8) {
    reg_alloc<224>();
    const int g = warp >> 2, w = warp & 3;
    uint32_t wq[20][4], wk[20][4], wo[4][4];
    const uint32_t foff = (uint32_t)((li >> 1) * 8 + lr) * 128 + (uint32_t)(((w * 2 + (li & 1)) ^ lr) * 16) + g * 8192;
    mbar_wait(bar + RB_W0 * 8, 0);
    TS(4);
#pragma unroll
    for (int j = 0; j < 20; j++) {
      ldsm_x4_t(wq[j], sb + R_V + foff + koff(j));
      ldsm_x4_t(wk[j], sb + R_H + foff + koff(j));
    }
    bar_sync(NB_INIT, 384);
    mbar_wait(bar + RB_W1 * 8, 0);
    mbar_wait(bar + RB_W2 * 8, 0);
    TS(5);
#pragma unroll
    for (int ks = 0; ks < 4; ks++) ldsm_x4_t(wo[ks], sb + R_WOSTG + foff + ks * 2048);
    bar_sync(NB_INIT, 384);
    const uint32_t wa = sb + R_WO + foff;
    uint32_t hmask;
    {
      uint32_t v = 0x100u;
      if (lane < 10) {
        const uint32_t* p = g_tab + ((lane >> 1) * 8 + warp) * 2 + (lane & 1);
        Spin sp;
        while (!((v = ld_acq(p)) & 0x100u)) sp.tick();
      }
      const int b = cta >> 5;
      hmask = (__ballot_sync(0xffffffffu, (v >> b) & 1) & 0x3FFu) | ((__ballot_sync(0xffffffffu, (v >> (3 + b)) & 1) & 0x3FFu) << 10);
    }

    TS(6);
    for (int s = -1; s < NSEG; s++) {
      if (s >= 0) {
        bar_sync(NB_MEM, 384);
        float aq[2][4], ak[2][4];
#pragma unroll
        for (int j = 0; j < 4; j++) { aq[0][j] = aq[1][j] = ak[0][j] = ak[1][j] = 0.f; }
        const uint32_t maddr = sb + R_MEM + (g * 64 + lane) * 16;
        {
          uint32_t b[3][4];
          ldsm_x4_t(b[0], maddr);
          ldsm_x4_t(b[1], maddr + 512);
#pragma unroll
          for (int kk = 0; kk < 10; kk++) {
            if (kk + 2 < 10) ldsm_x4_t(b[(kk + 2) % 3], maddr + ((kk + 2) >> 1) * 2048 + (kk & 1) * 512);
            mma16816(aq[0], wq[2 * kk], b[kk % 3][0], b[kk % 3][1]);
            mma16816(ak[0], wk[2 * kk], b[kk % 3][0], b[kk % 3][1]);
            mma16816(aq[1], wq[2 * kk + 1], b[kk % 3][2], b[kk % 3][3]);
            mma16816(ak[1], wk[2 * kk + 1], b[kk % 3][2], b[kk % 3][3]);
          }
        }
        {
          const uint32_t o = sb + (uint32_t)(warp * 256 + lane * 4);
          sts32(o + R_QS, pack_bf16(aq[0][0] + aq[1][0], aq[0][1] + aq[1][1]));
          sts32(o + R_QS + 128, pack_bf16(aq[0][2] + aq[1][2], aq[0][3] + aq[1][3]));
          sts32(o + R_KS, pack_bf16(ak[0][0] + ak[1][0], ak[0][1] + ak[1][1]));
          sts32(o + R_KS + 128, pack_bf16(ak[0][2] + ak[1][2], ak[0][3] + ak[1][3]));
        }
        if (warp == 0) TL(17);
        bar_sync(NB_QK, 256);
        if (warp < 6) {
          if (s < NSEG - 1) {
            const uint32_t qa = sb + R_QS + (li & 1) * 1024 + ((li >> 1) * 8 + lr) * 16;
            const uint32_t ka = (warp < 4) ? sb + R_KX + lane * 64 + ((warp ^ ((lr >> 1) & 3)) * 16) : sb + R_KS + (warp - 4) * 1024 + lane * 16;
            const uint32_t kstep = (warp < 4) ? 2048 : 512;
            float c[2][4];
#pragma unroll
            for (int j = 0; j < 4; j++) c[0][j] = c[1][j] = 0.f;
            uint32_t a[4][4], b[2][4];
            ldsm_x4_t(a[0], qa);
            ldsm_x4_t(b[0], ka);
            ldsm_x4_t(a[1], qa + 256);
            ldsm_x4_t(a[2], qa + 512);
            ldsm_x4_t(b[1], ka + kstep);
            ldsm_x4_t(a[3], qa + 768);
            mma16816(c[0], a[0], b[0][0], b[0][1]);
            mma16816(c[1], a[1], b[0][2], b[0][3]);
            mma16816(c[0], a[2], b[1][0], b[1][1]);
            mma16816(c[1], a[3], b[1][2], b[1][3]);
            const float v0 = (c[0][0] + c[0][2]) + (c[1][0] + c[1][2]);
            const float v1 = (c[0][1] + c[0][3]) + (c[1][1] + c[1][3]);
            const uint32_t dst = sb + R_SB + rank * 1536 + (warp >> 1) * 512 + lane * 16 + (warp & 1) * 8;
#pragma unroll
            for (int r = 0; r < 3; r++) st_async_v2(mapa(dst, r), mapa(bar + RB_S * 8, r), __float_as_uint(v0), __float_as_uint(v1));
            if (warp == 0) TL(19);
          }
        }
        if (VJ > 0) {
          const uint32_t va = sb + R_V + foff;
          float c0[4] = {0.f, 0.f, 0.f, 0.f}, c1[4] = {0.f, 0.f, 0.f, 0.f};
          uint32_t a[4][4], b[2][4];
          ldsm_x4_t(b[0], maddr);
#pragma unroll
          for (int i = 0; i < 4; i++) if (i < 2 * VJ) ldsm_x4_t(a[i], va + koff(i));
#pragma unroll
          for (int kk = 0; kk < VJ; kk++) {
            if (kk + 1 < VJ) ldsm_x4_t(b[(kk + 1) & 1], maddr + ((kk + 1) >> 1) * 2048 + ((kk + 1) & 1) * 512);
            mma16816(c0, a[(2 * kk) & 3], b[kk & 1][0], b[kk & 1][1]);
            if (2 * kk + 4 < 2 * VJ) ldsm_x4_t(a[(2 * kk) & 3], va + koff(2 * kk + 4));
            mma16816(c1, a[(2 * kk + 1) & 3], b[kk & 1][2], b[kk & 1][3]);
            if (2 * kk + 5 < 2 * VJ) ldsm_x4_t(a[(2 * kk + 1) & 3], va + koff(2 * kk + 5));
          }
          sts64(sb + R_VE + (tid & 127) * 16 + g * 8, pack_bf16(c0[0] + c1[0], c0[1] + c1[1]), pack_bf16(c0[2] + c1[2], c0[3] + c1[3]));
          bar_arrive(NB_X2, 384);
          if (warp == 0) TL(18);
        }
        if (s == NSEG - 1) {
          bar_sync(NB_O, 384);
          if (warp == 7) stage_km(sb, lane);
          bar_arrive(NB_P, 384);
          break;
        }
        {
#define FOFF(f) ((((f) >> 3) * 2 + ((f) & 1)) * 16384 + (((f) >> 1) & 3) * 2048)
          constexpr int PF = 5;
          uint32_t a[PF][4];
#pragma unroll
          for (int f = 0; f < PF; f++) ldsm_x4_t(a[f], wa + FOFF(f));
          uint32_t* pp = g_part + (size_t)((((s & 1) * 80 + warp * 2) * 3 + (cta >> 5)) * 2048 + (cta & 31) * 32 + lane);
          asm volatile("" : "+l"(pp));
          const uint32_t hm = opaque((hmask >> ((s & 1) * 10)) * 2 + ((s >> 1) & 1));
#define PSTORE(T, C)                                                                                  \
  st_half<(T) * 16 * 24576>(pp, hm & (2u << ((T) * 2)), (pack_bf16(C[0], C[1]) & ~1u) | (hm & 1u));  \
  st_half<(T) * 16 * 24576 + 24576>(pp, hm & (4u << ((T) * 2)), (pack_bf16(C[2], C[3]) & ~1u) | (hm & 1u));
#define BF(ks) b[(ks) >> 1][((ks) & 1) * 2], b[(ks) >> 1][((ks) & 1) * 2 + 1]
          bar_sync(NB_O, 384);
          uint32_t b[2][4];
          ldsm_x4_t(b[0], sb + R_OT + lane * 16);
          ldsm_x4_t(b[1], sb + R_OT + 512 + lane * 16);
          float c[5][4];
#pragma unroll
          for (int i = 0; i < 5; i++)
#pragma unroll
            for (int j = 0; j < 4; j++) c[i][j] = 0.f;
#pragma unroll
          for (int f = 0; f < 16; f++) {
            mma16816(c[(f >> 3) * 2 + (f & 1)], a[f % PF], BF((f >> 1) & 3));
            if (f + PF < 16) ldsm_x4_t(a[f % PF], wa + FOFF(f + PF));
            if (f >= 5 && f <= 11 && (f & 1)) mma16816(c[4], wo[(f - 5) >> 1], BF((f - 5) >> 1));
            if (f == 9) { PSTORE(0, c[0]); PSTORE(1, c[1]); }
            if (f == 13) { PSTORE(4, c[4]); }
          }
          PSTORE(2, c[2]);
          PSTORE(3, c[3]);
#undef PSTORE
#undef BF
#undef FOFF
          bar_arrive(NB_P, 384);
          if (warp == 0) { TL(21); TLG(22); }
        }
      }
      {
        mbar_wait(bar + RB_H * 8, (s + 1) & 1);
        const uint64_t dh = make_desc(sb + R_H, 128, 10240, 0);
        if (g == 0) {
          float kacc[16], vacc[16];
          const uint64_t dv = make_desc(sb + R_V, 8192, 1024, 1);
          wgmma_fence();
#pragma unroll
          for (int ks = 0; ks < VS; ks++) wgmma_ss_n32<1, 1>(vacc, dv + (uint64_t)(ks * 128), dh + (uint64_t)(ks * 16), ks > 0);
          wgmma_commit();
          bar_sync(NB_R, 384);
#pragma unroll
          for (int j = 0; j < XK1; j++) wgmma_rs_n32<1>(kacc, wk[j], dh + (uint64_t)((j >> 2) * 128 + (j & 3) * 16), j > 0);
          wgmma_commit();
#pragma unroll
          for (int ks = VS; ks < 40; ks++) wgmma_ss_n32<1, 1>(vacc, dv + (uint64_t)(ks * 128), dh + (uint64_t)(ks * 16), 1);
          wgmma_commit();
          wgmma_wait<1>();
          fence_regs(kacc);
#pragma unroll
          for (int j = 0; j < 4; j++)
            sts128(sb + R_XS + (j * 128 + tid) * 16, make_uint4(__float_as_uint(kacc[j * 4]), __float_as_uint(kacc[j * 4 + 1]),
                                                               __float_as_uint(kacc[j * 4 + 2]), __float_as_uint(kacc[j * 4 + 3])));
          bar_arrive(NB_X1, 256);
          wgmma_wait<0>();
          fence_regs(vacc);
          if (warp == 0 && s >= 0) TL(23);
          store_xt<1>(sb + R_VX, vacc, w, lane);
          fence_proxy_async();
          if (warp == 0 && s >= 0) TL(24);
        } else {
          float kacc[16];
          if (warp == 7 && s >= 0) stage_km(sb, lane);
          bar_sync(NB_R, 384);
          wgmma_fence();
#pragma unroll
          for (int j = 0; j < XK1; j++) wgmma_rs_n32<1>(kacc, wk[j], dh + (uint64_t)((j >> 2) * 128 + 64 + (j & 3) * 16), j > 0);
          wgmma_commit();
          wgmma_wait<0>();
          fence_regs(kacc);
          bar_sync(NB_X1, 256);
#pragma unroll
          for (int j = 0; j < 4; j++) {
            const uint4 p = lds128(sb + R_XS + (j * 128 + tid - 128) * 16);
            kacc[j * 4] += __uint_as_float(p.x); kacc[j * 4 + 1] += __uint_as_float(p.y);
            kacc[j * 4 + 2] += __uint_as_float(p.z); kacc[j * 4 + 3] += __uint_as_float(p.w);
          }
          store_xt<0>(sb + R_KX, kacc, w, lane);
          fence_proxy_async();
        }
      }
    }
  } else {
    reg_dealloc<56>();
    if (warp == 9) bar_arrive(NB_INIT, 384);
    if (tid == 288) {
      mbar_expect_tx(bar + RB_W2 * 8, 65536);
      for (int b = 0; b < 8; b++) tma_load_2d(sb + R_WO + b * 8192, &tmWo, bar + RB_W2 * 8, b * 64, cta * 64);
      __threadfence();
      asm volatile("red.relaxed.gpu.global.add.u32 [%0], 1;" ::"l"(g_cnt + CN_H) : "memory");
      st_relaxed32(g_tab + cta, (lds32(sb + R_BAR + 128) >> 16) | 0x100u);
    }
    if (warp != 9) bar_sync(NB_INIT, 384);
    if (tid == 256) {
      mbar_expect_tx(bar + RB_W1 * 8, 81920 + 16384);
      for (int b = 0; b < 2; b++) tma_load_2d(sb + R_WOSTG + b * 8192, &tmWo, bar + RB_W1 * 8, 512 + b * 64, cta * 64);
      for (int i = 0; i < 4; i++) tma_load_2d(sb + R_V + i * 20480, &tmWv, bar + RB_W1 * 8, cta * 64, i * 160);
      mbar_expect_tx(bar + RB_H * 8, 40960);
      wait_cnt(g_cnt + CN_H, 96);
      asm volatile("fence.proxy.async.global;" ::: "memory");
      bulk_g2s(sb + R_H, g_ht, 40960, bar + RB_H * 8);
    }
    mbar_wait(bar + RB_W1 * 8, 0);
    bar_sync(NB_INIT, 384);
    const float scale = 0.07216878364870322f * 1.4426950408889634f;
#define RELANE                                                                                                     \
  const int t = opaque(tid) & 127, lane = t & 31, li = lane >> 3, lr = lane & 7, w = t >> 5, g2 = w >> 1, tv = w; \
  (void)li; (void)lr; (void)g2; (void)tv
    bar_arrive(NB_R, 384);
    for (int s = 0; s < NSEG; s++) {
      {
        RELANE;
        const uint32_t* src = g_bc + (s & 3) * 6144 + t * 4;
        const uint32_t nm = (lds32(sb + R_BAR + 128) >> ((s & 3) * 3)) << 10;
        const uint32_t* sp3[3] = {src + (nm & 1024u), src + 2048 + ((nm >> 1) & 1024u), src + 4096 + ((nm >> 2) & 1024u)};
        uint4 v[5];
#pragma unroll
        for (int i = 0; i < 5; i++) v[i] = ld_relaxed128(sp3[i >> 1] + (i & 1) * 512);
        Spin sp;
        while (true) {
          uint32_t m = 0;
#pragma unroll
          for (int i = 0; i < 5; i++) m = max(m, max(max(v[i].x, v[i].y), max(v[i].z, v[i].w)));
          if (m != SENT) break;
          delay<PD3>();
#pragma unroll
          for (int i = 0; i < 5; i++) poll128(v[i], sp3[i >> 1] + (i & 1) * 512);
          sp.tick();
        }
        if (w == 0) { TL(0); TLG(10); }
#pragma unroll
        for (int i = 0; i < 5; i++) sts128(sb + R_MEM + (i * 128 + t) * 16, v[i]);
      }
      bar_sync(NB_MEM, 384);
      if (tid == 256) {
        bulk_s2g(g_k + (size_t)(s * 96 + cta) * 2048, sb + R_KX, 8192 / 2);
        bulk_s2g(g_v + (size_t)(s * 96 + cta) * 2048, sb + R_VX, 4096);
        if (s > 0) {
          bulk_s2g(g_km + (size_t)((s - 1) * 96 + cta) * 64 * NMEM, sb + R_KM, 1024);
          bulk_s2g(g_vm + (size_t)((s - 1) * 96 + cta) * 64 * NMEM, sb + R_VM, 1024);
        }
        bulk_commit();
        bulk_wait_read0();
      }
      uint32_t vw0, vw1;
      {
        RELANE;
        constexpr int NP = 2 * (10 - VJ);
        const uint32_t va = sb + R_V + (uint32_t)((li >> 1) * 8 + lr) * 128 + (uint32_t)(((w * 2 + (li & 1)) ^ lr) * 16), ma = sb + R_MEM + lane * 16;
#define VA(p, e) (va + ((p) & 1) * 8192 + koff(2 * (VJ + ((p) >> 1)) + (e)))
#define VB(p) (ma + ((p) & 1) * 1024 + ((VJ + ((p) >> 1)) >> 1) * 2048 + ((VJ + ((p) >> 1)) & 1) * 512)
        float c0[4] = {0.f, 0.f, 0.f, 0.f}, c1[4] = {0.f, 0.f, 0.f, 0.f};
        uint32_t a[4][4], b[2][4];
        if (NP > 0) {
          ldsm_x4_t(b[0], VB(0));
#pragma unroll
          for (int i = 0; i < 4; i++) ldsm_x4_t(a[i], VA(i >> 1, i & 1));
        }
#pragma unroll
        for (int p = 0; p < NP; p++) {
          if (p + 1 < NP) ldsm_x4_t(b[(p + 1) & 1], VB(p + 1));
          mma16816(c0, a[(2 * p) & 3], b[p & 1][0], b[p & 1][1]);
          if (p + 2 < NP) ldsm_x4_t(a[(2 * p) & 3], VA(p + 2, 0));
          mma16816(c1, a[(2 * p + 1) & 3], b[p & 1][2], b[p & 1][3]);
          if (p + 2 < NP) ldsm_x4_t(a[(2 * p + 1) & 3], VA(p + 2, 1));
        }
#undef VA
#undef VB
        vw0 = pack_bf16(c0[0] + c1[0], c0[1] + c1[1]);
        vw1 = pack_bf16(c0[2] + c1[2], c0[3] + c1[3]);
        if (w == 0) TL(25);
      }
#define VSTAGE                                                                                                           \
  {                                                                                                                      \
    const uint32_t vs = sb + R_VM + ((w >> 1) * 32 + (lane >> 3) * 8 + (w & 1) * 4 + ((lane >> 2) & 1)) * 16 + (lane & 3) * 4; \
    sts32(vs, pack_bf16(bf_lo(vm.x) + bf_lo(vm.z) + bf_lo(vw0), bf_hi(vm.x) + bf_hi(vm.z) + bf_hi(vw0)));                \
    sts32(vs + 32, pack_bf16(bf_lo(vm.y) + bf_lo(vm.w) + bf_lo(vw1), bf_hi(vm.y) + bf_hi(vm.w) + bf_hi(vw1)));           \
    fence_proxy_async();                                                                                                 \
  }
      if (s == NSEG - 1) {
        RELANE;
        if (VJ) bar_sync(NB_X2, 384);
        const uint4 vm = VJ ? lds128(sb + R_VE + t * 16) : make_uint4(0, 0, 0, 0);
        bar_arrive(NB_O, 384);
        VSTAGE;
        bar_sync(NB_P, 384);
        if (tid == 256) {
          seg_done(s - 1);
          bulk_s2g(g_km + (size_t)(s * 96 + cta) * 64 * NMEM, sb + R_KM, 1024);
          bulk_s2g(g_vm + (size_t)(s * 96 + cta) * 64 * NMEM, sb + R_VM, 1024);
          bulk_commit();
          seg_done(s);
        }
        break;
      }
      {
      RELANE;
      uint32_t ax[2][4];
      {
        const uint32_t vxa = sb + R_VX + (tv * 16 + (li & 1) * 8 + lr) * 64;
        const int vsw = ((lr >> 1) + tv * 2 + (li & 1)) & 3;
        ldsm_x4(ax[0], vxa + (((li >> 1) ^ vsw) * 16));
        ldsm_x4(ax[1], vxa + (((2 + (li >> 1)) ^ vsw) * 16));
      }
      if (w >= 2) __threadfence();
      mbar_wait(bar + RB_S * 8, s & 1);
      if (w == 0) TL(3);
      if (t == 96) {
        mbar_expect_tx(bar + RB_H * 8, 40960);
        bulk_g2s(sb + R_H, g_ht + (size_t)(s + 1) * SEG * DM, 40960, bar + RB_H * 8);
      }
      uint32_t pb[5];
      float sum;
      {
        const uint32_t sa = sb + R_SB + lane * 16;
        const uint4 a0 = lds128(sa), a1 = lds128(sa + 1536), a2 = lds128(sa + 3072);
        const uint4 b0 = lds128(sa + 512), b1 = lds128(sa + 2048), b2 = lds128(sa + 3584);
        const uint4 c0 = lds128(sa + 1024), c1 = lds128(sa + 2560), c2 = lds128(sa + 4096);
        float x[10];
#define F3(A, B, C) (__uint_as_float(A) + __uint_as_float(B) + __uint_as_float(C))
        x[0] = F3(a0.x, a1.x, a2.x); x[1] = F3(a0.y, a1.y, a2.y); x[2] = F3(a0.z, a1.z, a2.z); x[3] = F3(a0.w, a1.w, a2.w);
        x[4] = F3(b0.x, b1.x, b2.x); x[5] = F3(b0.y, b1.y, b2.y); x[6] = F3(b0.z, b1.z, b2.z); x[7] = F3(b0.w, b1.w, b2.w);
        x[8] = F3(c0.x, c1.x, c2.x) + F3(c0.z, c1.z, c2.z); x[9] = F3(c0.y, c1.y, c2.y) + F3(c0.w, c1.w, c2.w);
#undef F3
        float mx = fmaxf(fmaxf(fmaxf(x[0], x[1]), fmaxf(x[2], x[3])), fmaxf(fmaxf(x[4], x[5]), fmaxf(x[6], x[7])));
        mx = fmaxf(mx, fmaxf(x[8], x[9]));
        mx = fmaxf(mx, __shfl_xor_sync(0xffffffffu, mx, 1));
        mx = fmaxf(mx, __shfl_xor_sync(0xffffffffu, mx, 2));
        const float ms = -mx * scale;
#pragma unroll
        for (int i = 0; i < 10; i++) x[i] = ex2(fmaf(x[i], scale, ms));
#pragma unroll
        for (int i = 0; i < 5; i++) pb[i] = pack_bf16(x[2 * i], x[2 * i + 1]);
        sum = ((x[0] + x[1]) + (x[2] + x[3])) + ((x[4] + x[5]) + (x[6] + x[7])) + (x[8] + x[9]);
      }
      if (w == 0) TL(4);
      if (VJ) bar_sync(NB_X2, 384);
      const uint4 vm = VJ ? lds128(sb + R_VE + t * 16) : make_uint4(0, 0, 0, 0);
      if (w == 0) TL(2);
      {
        float o0[4] = {0.f, 0.f, 0.f, 0.f}, o1[4] = {0.f, 0.f, 0.f, 0.f};
        mma16816(o0, ax[0], pb[0], pb[1]);
        mma16816(o1, ax[1], pb[2], pb[3]);
        const uint32_t avm[4] = {vm.x, vm.y, vm.z, vm.w};
        if (VJ < 10) mma1688(o1, vw0, vw1, pb[4]);
        if (VJ) mma16816(o0, avm, pb[4], pb[4]);
        sum += __shfl_xor_sync(0xffffffffu, sum, 1);
        sum += __shfl_xor_sync(0xffffffffu, sum, 2);
        const float inv = __frcp_rn(sum);
        const float i0 = __shfl_sync(0xffffffffu, inv, (lane & 3) * 8), i1 = __shfl_sync(0xffffffffu, inv, (lane & 3) * 8 + 4);
        const uint32_t oo = sb + R_OT + tv * 256 + lane * 4;
        sts32(oo, pack_bf16((o0[0] + o1[0]) * i0, (o0[1] + o1[1]) * i1));
        sts32(oo + 128, pack_bf16((o0[2] + o1[2]) * i0, (o0[3] + o1[3]) * i1));
      }
      bar_arrive(NB_O, 384);
      if (w == 0) TL(6);
      VSTAGE;
      if (t == 0) {
        mbar_expect_tx(bar + RB_S * 8, 4608);
        if (s > 0) seg_done(s - 1);
      }
      }
      if (cta >= 80) { bar_sync(NB_P, 384); bar_arrive(NB_R, 384); delay<PD2>(); }
      if (cta < 80) {
        RELANE;
        const uint32_t* src = g_part + (size_t)((s & 1) * 80 + cta) * 6144 + t * 4;
        const uint32_t nm = (lds32(sb + R_BAR + 128) >> (16 + (s & 1) * 3)) << 10;
        const uint32_t* sp3[3] = {src + (nm & 1024u), src + 2048 + ((nm >> 1) & 1024u), src + 4096 + ((nm >> 2) & 1024u)};
        const uint32_t tagx = (s >> 1) & 1;
        bar_sync(NB_P, 384);
        delay<PD0>();
        uint4 v[6];
#pragma unroll
        for (int i = 0; i < 6; i++) v[i] = ld_relaxed128(sp3[i >> 1] + (i & 1) * 512);
        Spin sp;
        while (true) {
          uint32_t bad[6], any = 0;
#pragma unroll
          for (int i = 0; i < 6; i++) {
            bad[i] = (((v[i].x ^ tagx) | (v[i].y ^ tagx)) | ((v[i].z ^ tagx) | (v[i].w ^ tagx))) & 1u;
            any |= bad[i];
          }
          if (!__any_sync(0xffffffffu, any)) break;
#pragma unroll
          for (int i = 0; i < 6; i++) poll128_if(v[i], sp3[i >> 1] + (i & 1) * 512, bad[i]);
          sp.tick();
        }
        if (w == 0) { TL(7); TLG(11); }
        if (RPOS == 0) bar_arrive(NB_R, 384);
        const uint32_t cst = tagx ? 0xFFFF8000u : 0x8000u;
        float f[8];
#pragma unroll
        for (int j = 0; j < 8; j++) f[j] = 0.f;
#pragma unroll
        for (int i = 0; i < 6; i++) {
          f[0] += __uint_as_float((v[i].x << 16) + cst); f[1] += bf_hi(v[i].x);
          f[2] += __uint_as_float((v[i].y << 16) + cst); f[3] += bf_hi(v[i].y);
          f[4] += __uint_as_float((v[i].z << 16) + cst); f[5] += bf_hi(v[i].z);
          f[6] += __uint_as_float((v[i].w << 16) + cst); f[7] += bf_hi(v[i].w);
        }
        const bool u1 = lane & 16, u2 = lane & 8;
        float e[4], d[2];
#pragma unroll
        for (int j = 0; j < 4; j++) {
          const float snd = u1 ? f[j] : f[4 + j], kp = u1 ? f[4 + j] : f[j];
          e[j] = kp + __shfl_xor_sync(0xffffffffu, snd, 16);
        }
#pragma unroll
        for (int j = 0; j < 2; j++) {
          const float snd = u2 ? e[j] : e[2 + j], kp = u2 ? e[2 + j] : e[j];
          d[j] = kp + __shfl_xor_sync(0xffffffffu, snd, 8);
        }
        const int wd = (lane & 7) * 4 + (lane >> 4) * 2 + ((lane >> 3) & 1);
        sts64(sb + R_VE + w * 256 + wd * 8, __float_as_uint(d[0]), __float_as_uint(d[1]));
        bar_sync(NB_G1, 128);
        if (RPOS == 1) bar_arrive(NB_R, 384);
        uint32_t* dst = g_bc + (cta >> 5) * 2048 + (w & 1) * 1024 + (cta & 31) * 32 + lane;
        if (w < 2) {
          const uint2 p0 = lds64(sb + R_VE + lane * 8), p1 = lds64(sb + R_VE + 256 + lane * 8);
          const uint2 p2 = lds64(sb + R_VE + 512 + lane * 8), p3 = lds64(sb + R_VE + 768 + lane * 8);
          uint32_t wv = pack_bf16((__uint_as_float(p0.x) + __uint_as_float(p1.x)) + (__uint_as_float(p2.x) + __uint_as_float(p3.x)),
                                  (__uint_as_float(p0.y) + __uint_as_float(p1.y)) + (__uint_as_float(p2.y) + __uint_as_float(p3.y)));
          if (wv == SENT) wv = 0x7FFF7FFFu;
          st_relaxed32(dst + ((s + 1) & 3) * 6144, wv);
          if (RPOS == 2) bar_arrive(NB_R, 384);
        } else {
          st_relaxed32(dst + ((s + 3) & 3) * 6144, SENT);
          if (RPOS == 2) bar_arrive(NB_R, 384);
        }
        if (w == 0) { TL(8); TLG(12); }
        delay<PD1>();
      }
    }
  }
  cluster_sync_all();
  TS(7);
}

constexpr int C_ST = 4, C_STAGE = 57344;
constexpr int C_BAR = C_ST * C_STAGE;
constexpr int C_DESC = C_BAR + 64;
constexpr int C_REQ = C_BAR + 96;
constexpr int C_SIG = C_BAR + 128;
constexpr int C_SNAP = C_BAR + 256;
constexpr int C_SMEM = C_SNAP + 1024;
static_assert(C_SMEM <= 232448, "smem");
enum { T_FIN = 0, T_F2 = 1, T_F1 = 2, T_LN = 3, T_WO = 4, T_ATT = 5, T_Q = 6, T_Z = 7, T_EXIT = 8 };
#define TBK 10
#define TBW 14
#define PRECLAIM 1
#define TBA 15
static_assert(TBA <= 15 && TBW <= 14 && TBK <= 13, "static tail lists");
#define NSL 100
#define ONCE 0
#define UA 16
#define UW 16
constexpr int N_QZ = 16 + 384;

__device__ __forceinline__ void mbar_wait_nt(uint32_t bar, uint32_t parity) {
  while (!mbar_try(bar, parity)) {}
}
__device__ __forceinline__ uint32_t lds8(uint32_t addr) {
  uint32_t v;
  asm volatile("ld.shared.u8 %0, [%1];" : "=r"(v) : "r"(addr) : "memory");
  return v;
}
__device__ __forceinline__ void signal(uint32_t sb, uint32_t& nsig, int cidx, int tid) {
  __syncwarp();
  if ((tid & 31) == 0) {
    while (nsig - lds32(sb + C_SIG + 96) >= 8u) {}
    if (tid == 0) sts32(sb + C_SIG + 64 + (nsig & 7) * 4, cidx);
    mbar_arrive(sb + C_SIG + (nsig & 7) * 8);
  }
  nsig++;
}
__device__ __forceinline__ uint2 pair_x(uint32_t a, uint32_t b, bool odd) {
  const uint32_t r = __shfl_xor_sync(0xffffffffu, odd ? a : b, 1);
  return odd ? make_uint2(r, b) : make_uint2(a, r);
}
__device__ __forceinline__ void red4(float4* p, float a, float b, float c, float d) {
  asm volatile("red.relaxed.gpu.global.add.v4.f32 [%0], {%1,%2,%3,%4};" ::"l"(p), "f"(a), "f"(b), "f"(c), "f"(d) : "memory");
}
__device__ __forceinline__ uint4 ld_acq128(const uint32_t* p) {
  uint4 v;
  asm volatile("ld.acquire.gpu.global.v4.b32 {%0,%1,%2,%3}, [%4];" : "=r"(v.x), "=r"(v.y), "=r"(v.z), "=r"(v.w) : "l"(p) : "memory");
  return v;
}
__device__ __forceinline__ void group_dep(int q, int g, int& c0, uint32_t& n0, int& c1, uint32_t& n1) {
  c1 = CN_Z; n1 = 0;
  if (q == T_F2) { c0 = CN_F1 + g; n0 = g >= TBK ? 24 : 6; }
  else if (q == T_F1) { c0 = CN_LN + g; n0 = g >= TBK ? 8 : 4; }
  else if (q == T_LN) { c0 = CN_WO + g; n0 = g >= TBW ? 60 : 8; }
  else if (q == T_WO) { c0 = CN_ATT + g; n0 = g >= TBA ? 64 : 32; c1 = CN_Z + g; n1 = 1; }
  else { c0 = CN_SEG + g; n0 = 96; c1 = CN_Q + (g >> 2); n1 = 24; }
}
__device__ __forceinline__ bool group_ready(uint32_t snap, int q, int g) {
  int c0, c1;
  uint32_t n0, n1;
  group_dep(q, g, c0, n0, c1, n1);
  return lds32(snap + c0 * 4) >= n0 && lds32(snap + c1 * 4) >= n1;
}
__device__ __forceinline__ bool group_soon(uint32_t snap, int q, int g) {
  int c0, c1;
  uint32_t n0, n1;
  group_dep(q, g, c0, n0, c1, n1);
  if (lds32(snap + c1 * 4) < n1) return false;
  if (q == T_ATT) return g >= NSEG - 2;
  const uint32_t cb = snap + CN_CLAIM * 4 + (q + 1) * 16;
  if (q == T_WO) return __vcmpgeu4(lds32(cb + g * 4), (n0 >> 2) * 0x01010101u) == 0xFFFFFFFFu && group_ready(snap, T_ATT, g * 4 + 3);
  return lds8(cb + g) >= n0 && group_ready(snap, q + 1, g);
}

template <int NA, int NB>
__device__ __forceinline__ void gemm_loop(float (&a0)[NA / 2], float (&a1)[NB ? NB / 2 : 2], uint32_t sb, uint32_t& it, int nk, int wg, int lane) {
#pragma unroll
  for (int i = 0; i < NA / 2; i++) a0[i] = 0.f;
#pragma unroll
  for (int i = 0; i < (NB ? NB / 2 : 2); i++) a1[i] = 0.f;
  for (int kb = 0; kb < nk; kb++, it++) {
    const uint32_t st = it & 3;
    if (kb) mbar_wait_nt(sb + C_BAR + st * 8, (it >> 2) & 1);
    const uint32_t sa = sb + st * C_STAGE;
    const uint64_t da = make_desc(sa + wg * 8192, 16, 1024, 1), db = make_desc(sa + 16384, 8192, 1024, 1);
    wgmma_fence();
#pragma unroll
    for (int kk = 0; kk < 4; kk++) {
      if constexpr (NA == 256) wgmma_ss_n256<0, 1>(a0, da + kk * 2, db + kk * 128, 1);
      else if constexpr (NA == 128) wgmma_ss_n128<0, 1>(a0, da + kk * 2, db + kk * 128, 1);
      else if constexpr (NA == 64) {
        wgmma_ss_n64<0, 1>(a0, da + kk * 2, db + kk * 128, 1);
        wgmma_ss_n64<0, 1>(a0, da + 1536 + kk * 2, db + 1536 + kk * 128, 1);
      } else wgmma_ss_n192<0, 1>(a0, da + kk * 2, db + kk * 128, 1);
      if constexpr (NB == 128) wgmma_ss_n128<0, 1>(a1, da + kk * 2, db + (NA / 64) * 512 + kk * 128, 1);
    }
    wgmma_commit();
    if (kb) {
      wgmma_wait<1>();
      if (lane == 0) mbar_arrive(sb + C_BAR + 32 + ((it - 1) & 3) * 8);
    }
  }
  wgmma_wait<0>();
  if (lane == 0) mbar_arrive(sb + C_BAR + 32 + ((it - 1) & 3) * 8);
  fence_regs(a0);
  fence_regs(a1);
}

template <int NP>
__device__ __forceinline__ void ep_f1(const float (&acc)[NP * 8], int row0, int n0, int lane) {
  const bool odd = lane & 1;
  uint2* dst = reinterpret_cast<uint2*>(g_f + (size_t)(row0 + (lane >> 2)) * FF + n0 + (lane & 1) * 8 + (lane & 2) * 2);
#pragma unroll
  for (int j = 0; j < NP; j++) {
    float v[8];
#pragma unroll
    for (int e = 0; e < 8; e++) {
      const float a = round_bf16(acc[j * 8 + e]);
      v[e] = __fdividef(a, 1.f + __expf(-a));
    }
    dst[j * 4] = pair_x(pack_bf16(v[0], v[1]), pack_bf16(v[4], v[5]), odd);
    dst[j * 4 + 2 * FF] = pair_x(pack_bf16(v[2], v[3]), pack_bf16(v[6], v[7]), odd);
  }
}
template <int R2>
__device__ __forceinline__ void ln_task(const bf16* __restrict__ x, int rt, uint32_t scr, uint32_t ebar, int warp, int lane, uint32_t epi, uint32_t ntask) {
  const bool odd = lane & 1;
          float v[R2][10][4];
          {
            uint32_t xr[R2][10][2];
#pragma unroll
            for (int r2 = 0; r2 < R2; r2++) {
              const size_t fo = ((size_t)(rt + r2) * 80 + warp * 10) * 32 + lane;
              const uint32_t* xs = reinterpret_cast<const uint32_t*>(x + (size_t)((rt + r2) * 16 + (lane >> 2)) * DM + warp * 80 + (lane & 3) * 2);
#pragma unroll
              for (int j = 0; j < 10; j++) {
                const float4 a = __ldcg(g_acc + fo + j * 32);
                v[r2][j][0] = a.x; v[r2][j][1] = a.y; v[r2][j][2] = a.z; v[r2][j][3] = a.w;
                xr[r2][j][0] = __ldg(xs + j * 4);
                xr[r2][j][1] = __ldg(xs + j * 4 + 4 * DM);
              }
            }
#pragma unroll
            for (int r2 = 0; r2 < R2; r2++) {
              const size_t fo = ((size_t)(rt + r2) * 80 + warp * 10) * 32 + lane;
#pragma unroll
              for (int j = 0; j < 10; j++) {
                const float2 g = __ldg(reinterpret_cast<const float2*>(g_mod + 2 * DM + warp * 80 + j * 8 + (lane & 3) * 2));
                const uint2 o = make_uint2(pack_bf16(bf_lo(xr[r2][j][0]) + g.x * v[r2][j][0], bf_hi(xr[r2][j][0]) + g.y * v[r2][j][1]),
                                           pack_bf16(bf_lo(xr[r2][j][1]) + g.x * v[r2][j][2], bf_hi(xr[r2][j][1]) + g.y * v[r2][j][3]));
                g_x1f[fo + j * 32] = o;
                v[r2][j][0] = bf_lo(o.x); v[r2][j][1] = bf_hi(o.x); v[r2][j][2] = bf_lo(o.y); v[r2][j][3] = bf_hi(o.y);
              }
            }
          }
          float mean[R2 * 2], rstd[R2 * 2];
          if (warp == 0 && lane == 0) sts32(epi, ntask);
#pragma unroll
          for (int pass = 0; pass < 2; pass++) {
#pragma unroll
            for (int r = 0; r < R2 * 2; r++) {
              float sacc = 0.f;
#pragma unroll
              for (int j = 0; j < 10; j++) {
                const float d0 = v[r >> 1][j][(r & 1) * 2], d1 = v[r >> 1][j][(r & 1) * 2 + 1];
                if (pass == 0) sacc += d0 + d1;
                else sacc += (d0 - mean[r]) * (d0 - mean[r]) + (d1 - mean[r]) * (d1 - mean[r]);
              }
              sacc += __shfl_xor_sync(0xffffffffu, sacc, 1);
              sacc += __shfl_xor_sync(0xffffffffu, sacc, 2);
              if ((lane & 3) == 0) sts32(scr + pass * 1024 + (r * 8 + (lane >> 2)) * 32 + warp * 4, __float_as_uint(sacc));
            }
            bar_sync(1, 256);
#pragma unroll
            for (int r = 0; r < R2 * 2; r++) {
              const uint4 p0 = lds128(scr + pass * 1024 + (r * 8 + (lane >> 2)) * 32), p1 = lds128(scr + pass * 1024 + (r * 8 + (lane >> 2)) * 32 + 16);
              const float t = ((__uint_as_float(p0.x) + __uint_as_float(p0.y)) + (__uint_as_float(p0.z) + __uint_as_float(p0.w))) +
                              ((__uint_as_float(p1.x) + __uint_as_float(p1.y)) + (__uint_as_float(p1.z) + __uint_as_float(p1.w)));
              if (pass == 0) mean[r] = t * (1.f / DM);
              else rstd[r] = rsqrtf(t * (1.f / DM) + 1e-5f);
            }
          }
          fence_proxy_async();
          __syncwarp();
          if (lane == 0) mbar_arrive(ebar);
#pragma unroll
          for (int r2 = 0; r2 < R2; r2++) {
            uint2* dst = reinterpret_cast<uint2*>(g_h2 + (size_t)((rt + r2) * 16 + (lane >> 2)) * DM + warp * 80 + (lane & 1) * 8 + (lane & 2) * 2);
#pragma unroll
            for (int j = 0; j < 10; j += 2) {
              uint32_t w[2][2];
#pragma unroll
              for (int e = 0; e < 2; e++) {
                const float2 sc = __ldg(reinterpret_cast<const float2*>(g_mod + 4 * DM + warp * 80 + (j + e) * 8 + (lane & 3) * 2));
                const float2 sh = __ldg(reinterpret_cast<const float2*>(g_mod + 3 * DM + warp * 80 + (j + e) * 8 + (lane & 3) * 2));
                w[e][0] = pack_bf16((v[r2][j + e][0] - mean[r2 * 2]) * rstd[r2 * 2] * (1.f + sc.x) + sh.x,
                                    (v[r2][j + e][1] - mean[r2 * 2]) * rstd[r2 * 2] * (1.f + sc.y) + sh.y);
                w[e][1] = pack_bf16((v[r2][j + e][2] - mean[r2 * 2 + 1]) * rstd[r2 * 2 + 1] * (1.f + sc.x) + sh.x,
                                    (v[r2][j + e][3] - mean[r2 * 2 + 1]) * rstd[r2 * 2 + 1] * (1.f + sc.y) + sh.y);
              }
              dst[j * 2] = pair_x(w[0][0], w[1][0], odd);
              dst[j * 2 + 2 * DM] = pair_x(w[0][1], w[1][1], odd);
            }
          }
}

__global__ __launch_bounds__(384, 1) void k_cons(const __grid_constant__ CUtensorMap tA_h, const __grid_constant__ CUtensorMap tB_q,
                                                 const __grid_constant__ CUtensorMap tA_o, const __grid_constant__ CUtensorMap tB_o,
                                                 const __grid_constant__ CUtensorMap tA_h2, const __grid_constant__ CUtensorMap tB_w1,
                                                 const __grid_constant__ CUtensorMap tA_f, const __grid_constant__ CUtensorMap tB_w2,
                                                 const bf16* __restrict__ x, bf16* __restrict__ out) {
  extern __shared__ __align__(1024) uint8_t smem_raw[];
  const uint32_t sb = smem_u32(smem_raw);
  const int tid = threadIdx.x, lane = tid & 31;
  const int warp = __shfl_sync(0xffffffffu, tid >> 5, 0);
  if (tid == 0) {
    for (int i = 0; i < C_ST; i++) {
      mbar_init(sb + C_BAR + i * 8, 1);
      mbar_init(sb + C_BAR + 32 + i * 8, 8);
    }
    for (int i = 0; i < 8; i++) mbar_init(sb + C_SIG + i * 8, 8);
    sts32(sb + C_SIG + 96, 0);
    sts32(sb + C_REQ + 24, 0);
    mbar_init(sb + C_REQ, 1);
    mbar_init(sb + C_REQ + 8, 1);
    fence_mbar_init();
  }
  __syncthreads();
  if (warp >= 8) {
    reg_dealloc<56>();
    if (warp == 8) {
      if (lane == 0) {
        uint32_t it = 0;
        mbar_arrive(sb + C_REQ);
        for (uint32_t n = 0;; n++) {
          mbar_wait(sb + C_REQ + 8, n & 1);
          const uint2 tk = lds64(sb + C_REQ + 16);
          const int type = tk.x, idx = tk.y;
          int nst = 1, m0 = 0, n0 = 0, k0 = 0, nb = 0;
          const CUtensorMap *ta = nullptr, *tb = nullptr;
          if (type == T_Q) { ta = &tA_h; tb = &tB_q; m0 = (idx / 24) * 128; n0 = (idx % 24) * 256; nst = 10; nb = 4; }
          else if (type == T_ATT) nst = (idx >> 6) >= TBA ? 2 : 4;
          else if (type <= T_WO && type != T_LN) {
            const int i = idx & 63;
            const bool fine = (idx >> 6) >= (type == T_WO ? TBW : TBK);
            m0 = (idx >> 6) * 128;
            if (type == T_F1) { ta = &tA_h2; tb = &tB_w1; n0 = i * (fine ? 64 : 256); nst = fine ? 5 : 10; nb = fine ? 1 : 4; }
            else if (type == T_F2) { ta = &tA_f; tb = &tB_w2; n0 = i * (fine ? 64 : 320); nst = fine ? 12 : 24; nb = fine ? 1 : 5; }
            else if (fine) { ta = &tA_o; tb = &tB_o; n0 = (i % 5) * 128; k0 = (i / 5) * 8; nst = 8; nb = 2; }
            else { ta = &tA_o; tb = &tB_o; n0 = (i & 1) * 320; k0 = (i >> 1) * 24; nst = 24; nb = 5; }
          }
          const int ireq = type == T_EXIT ? -1 : max(nst - 3, 0);
          for (int i = 0; i < nst; i++, it++) {
            const uint32_t st = it & 3, fb = sb + C_BAR + st * 8, sa = sb + st * C_STAGE;
            mbar_wait(fb + 32, ((it >> 2) & 1) ^ 1);
            if (i == ireq) mbar_arrive(sb + C_REQ);
            if (i == 0) sts64(sb + C_DESC + st * 8, type, idx);
            if (nb == 1) {
              mbar_expect_tx(fb, 49152);
              for (int b = 0; b < 2; b++) {
                tma_load_2d(sa + b * 24576, ta, fb, (i * 2 + b) * 64, m0);
                tma_load_2d(sa + b * 24576 + 16384, tb, fb, n0, (i * 2 + b) * 64);
              }
            } else if (nb) {
              mbar_expect_tx(fb, 16384 + nb * 8192);
              tma_load_2d(sa, ta, fb, (k0 + i) * 64, m0);
              for (int b = 0; b < nb; b++) tma_load_2d(sa + 16384 + b * 8192, tb, fb, n0 + b * 64, (k0 + i) * 64);
            } else if (type == T_ATT) {
              const size_t u = (size_t)(idx >> 4) * 96 + ((idx & 15) * nst + i) * 3;
              mbar_expect_tx(fb, 30720 + 12288);
              const bf16* qs = g_q + ((size_t)(idx >> 4) * 768 + ((idx & 15) * nst + i) * 12) * 256;
              bulk_g2s(sa + 30720, qs, 6144, fb);
              bulk_g2s(sa + 36864, qs + 384 * 256, 6144, fb);
              bulk_g2s(sa, g_k + u * 2048, 12288, fb);
              bulk_g2s(sa + 12288, g_v + u * 2048, 12288, fb);
              bulk_g2s(sa + 24576, g_km + u * 512, 3072, fb);
              bulk_g2s(sa + 27648, g_vm + u * 512, 3072, fb);
            } else {
              mbar_arrive(fb);
            }
          }
          if (type == T_EXIT) {
            mbar_wait(sb + C_BAR + 32 + ((it - 1) & 3) * 8, ((it - 1) >> 2) & 1);
            break;
          }
        }
      }
      __syncwarp();
    } else if (warp == 10) {
      const int q = lane < 24 ? lane >> 2 : T_Q;
      const int gs0 = q == T_F1 ? 6 : q == T_LN ? 4 : q == T_F2 ? 2 : 8;
      const int gs1 = q == T_F1 ? 24 : q == T_LN ? 8 : q == T_F2 ? 10 : q == T_WO ? 60 : 16;
      const int gfine = q == T_ATT ? TBA * 4 : q == T_WO ? TBW : TBK;
      const int ngr = q == T_FIN ? 0 : q == T_ATT ? 64 : 16;
      const uint32_t snap = sb + C_SNAP, cbase = snap + CN_CLAIM * 4 + q * 16;
      int gbase = 0;
      const uint32_t szs = (uint32_t)(lane < 16 ? ((lane & 15) >= TBK ? 10 : 2) : ((lane & 15) >= TBK ? 24 : 6)) |
                           (uint32_t)(lane < 16 ? ((lane & 15) >= TBK ? 8 : 4) : ((lane & 15) >= TBW ? 60 : 8)) << 8 |
                           (uint32_t)(lane >= TBA * 4 ? 16 : 8) << 16 | (uint32_t)(lane + 32 >= TBA * 4 ? 16 : 8) << 24;
      int sk = blockIdx.x >= 36 ? 0 : 5;
      bool longp = false;
      for (uint32_t n = 0;; n++) {
        mbar_wait_nt(sb + C_REQ, n & 1);
        int type = T_EXIT, idx = 0;
        const int lr = blockIdx.x - 36, m32 = lr & 31;
        if (sk == 1 && (lr & 63) >= 60 - (lr >> 6) * 32) sk = 2;
        if (sk == 2 && (m32 < 8 || !ONCE)) sk = 3;
        if (sk == 4 && m32 >= 10) sk = 5;
        const bool once = sk == 2;
        while (sk == 2 || sk == 5) {
          {
            const uint4 s0 = ld_relaxed128(g_cnt + lane * 4), s1 = ld_relaxed128(g_cnt + (32 + lane) * 4);
            sts128(snap + lane * 16, s0);
            sts128(snap + (32 + lane) * 16, s1);
          }
          __syncwarp();
          bool ready = false, soon = false;
          int g = 0, gsz = 0;
          {
            const uint32_t cb = snap + CN_CLAIM * 4 + 16 + lane;
            const uint32_t m0 = __ballot_sync(0xffffffffu, lds8(cb) < (szs & 255u));
            const uint32_t m1 = __ballot_sync(0xffffffffu, lds8(cb + 32) < ((szs >> 8) & 255u));
            const uint32_t m2 = __ballot_sync(0xffffffffu, lds8(cb + 64) < ((szs >> 16) & 255u));
            const uint32_t m3 = __ballot_sync(0xffffffffu, lds8(cb + 96) < (szs >> 24));
            const uint32_t mm = ((q < T_LN ? m0 : m1) >> ((q & 1) ? 0 : 16)) & 0xFFFFu;
            gbase = q == T_ATT ? (m2 ? __ffs(m2) - 1 : m3 ? __ffs(m3) + 31 : 64) : (mm ? __ffs(mm) - 1 : 16);
          }
          int avail = 0;
          if (lane < 24) {
            g = gbase + (lane & 3);
            gsz = g >= gfine ? gs1 : gs0;
            if (g < ngr) avail = gsz - (int)lds8(cbase + g);
            if (avail > 0) {
              ready = group_ready(snap, q, g);
              soon = PRECLAIM && lds32(snap + (CN_SEG + NSEG - 3) * 4) >= 96u && group_soon(snap, q, g);
            }
          } else if (lane == 24) {
            const uint32_t qh = lds32(snap + CN_QH * 4);
            ready = qh < (uint32_t)N_QZ && lds32(snap + CN_H * 4) >= 96u;
            gbase = qh < (uint32_t)N_QZ ? 0 : 99;
          }
          uint32_t rm = __ballot_sync(0xffffffffu, ready);
          const bool more = __any_sync(0xffffffffu, lane <= 24 && gbase < ngr);
          if (!rm && !more) break;
          int got = -1;
          const uint32_t cm = __ballot_sync(0xffffffffu, g < (q == T_ATT ? TBW * 4 : gfine)) & 0xFFFFFFu;
          const uint32_t um = __ballot_sync(0xffffffffu, q == T_ATT ? g >= UA * 4 : q == T_WO && g >= UW) & 0xFFFFFFu;
          {
            const bool endp = lds32(snap + (CN_SEG + NSEG - 1) * 4) >= 96u;
            const uint32_t epi = lds32(sb + C_REQ + 24);
            if (epi + ((longp || endp) ? 0u : 1u) < n) rm &= endp ? 0u : (cm | 0x1000000u);
            const uint32_t sm = __ballot_sync(0xffffffffu, soon);
            if (once) {
              rm &= ~cm & 0xFFFFFFu;
              if (epi >= n) sk = 3;
            } else if (epi >= n) rm |= rm ? sm & (0xFu << (T_ATT * 4)) : sm;
          }
          while (rm) {
            uint32_t m = (rm & um) ? 0u : rm & cm;
            if (!m) {
              m = (rm & um) ? rm & um : rm & 0xFFFFFFu;
              m = m ? m & (0xFu << ((31 - __clz(m)) & 28)) : rm;
            }
            const int sel = __ffs(m) - 1;
            rm &= ~(1u << sel);
            uint32_t cl = 0;
            if (lane == sel) cl = atomicAdd(g_cnt + (lane < 24 ? CN_CLAIM + q * 4 + (g >> 2) : CN_QH), lane < 24 ? 1u << ((g & 3) * 8) : 1u);
            const int qs = __shfl_sync(0xffffffffu, q, sel), gs = __shfl_sync(0xffffffffu, g, sel);
            int c0 = CN_H, c1 = CN_H;
            uint32_t n0 = 0, n1, cv = 0;
            if (sel < 24) group_dep(qs, gs, c0, n0, c1, n1);
            if (lane < 2) cv = ld_acq(g_cnt + (lane ? c1 : c0));
            if (lane == sel) {
              if (lane < 24) {
                const int i = (cl >> ((g & 3) * 8)) & 255u;
                if (i < gsz) got = g * (q == T_ATT ? 16 : 64) + i;
              } else if (cl < (uint32_t)N_QZ) got = cl;
            }
            got = __shfl_sync(0xffffffffu, got, sel);
            if (got >= 0) {
              type = qs;
              idx = got;
              if (lane == 0 && cv < n0) wait_cnt(g_cnt + c0, n0);
              __syncwarp();
              break;
            }
          }
          if (got >= 0) break;
          __nanosleep(NSL);
        }
        if (once) sk = 3;
        if (type == T_EXIT && sk < 5) {
          const int b = lr < 32 ? 15 : lr < 64 ? 13 : 14;
          type = sk == 0 ? (lr < 64 ? T_ATT : T_WO) : sk == 1 ? T_WO : sk == 3 ? (m32 < 8 ? T_LN : T_F1) : T_F2;
          idx = sk == 0 ? (lr < 64 ? 1023 - lr : 14 * 64 + m32) : sk == 1 ? (lr < 64 ? 15 * 64 + lr : 14 * 64 + 32 + m32) : b * 64 + (sk == 3 && m32 >= 8 ? m32 - 8 : m32);
          int c0, c1;
          uint32_t n0, n1;
          group_dep(type, type == T_ATT ? idx >> 4 : idx >> 6, c0, n0, c1, n1);
          if (lane < 2) wait_cnt(g_cnt + (lane ? c1 : c0), lane ? n1 : n0);
          __syncwarp();
          sk++;
        }
        longp = type == T_Q || (type != T_ATT && (idx >> 6) < (type == T_WO ? TBW : TBK));
        if (type == T_Q) { if (idx < 16) type = T_Z; else idx -= 16; }
        if (lane == 0) {
          asm volatile("fence.proxy.async.global;" ::: "memory");
          sts64(sb + C_REQ + 16, type, idx);
          mbar_arrive(sb + C_REQ + 8);
        }
        __syncwarp();
        if (type == T_EXIT) break;
      }
    } else if (warp == 11) {
      const CUtensorMap* tm = lane == 0 ? &tA_h : lane == 1 ? &tB_q : lane == 2 ? &tA_o : lane == 3 ? &tB_o : lane == 4 ? &tA_h2 : lane == 5 ? &tB_w1 : lane == 6 ? &tA_f : &tB_w2;
      if (lane < 8) asm volatile("prefetch.tensormap [%0];" ::"l"((uint64_t)tm) : "memory");
      __syncwarp();
    } else if (warp == 9) {
      for (uint32_t n = 0;; n++) {
        mbar_wait_nt(sb + C_SIG + (n & 7) * 8, (n >> 3) & 1);
        const int c = lds32(sb + C_SIG + 64 + (n & 7) * 4);
        if (c < 0) break;
        if (lane == 0) {
          asm volatile("red.release.gpu.global.add.u32 [%0], 1;" ::"l"(g_cnt + c) : "memory");
          sts32(sb + C_SIG + 96, n + 1);
        }
        __syncwarp();
      }
    }
  } else {
    reg_alloc<224>();
    uint32_t it = 0, nsig = 0, ntask = 0;
    while (true) {
      const int tid = opaque(threadIdx.x), lane = tid & 31;
      const int warp = __shfl_sync(0xffffffffu, tid >> 5, 0), wg = warp >> 2;
      mbar_wait_nt(sb + C_BAR + (it & 3) * 8, (it >> 2) & 1);
      const uint2 ds = lds64(sb + C_DESC + (it & 3) * 8);
      const int type = __shfl_sync(0xffffffffu, ds.x, 0), idx = __shfl_sync(0xffffffffu, ds.y, 0);
      if (type == T_EXIT) {
        signal(sb, nsig, -1, tid);
        if (lane == 0) mbar_arrive(sb + C_BAR + 32 + (it & 3) * 8);
        break;
      }
      const int blk = idx >> 6, ti = idx & 63;
      ntask++;
      if (type <= T_WO && type != T_LN && blk >= (type == T_WO ? TBW : TBK)) {
        if (type == T_WO) {
          float acc[64], dum[2];
          gemm_loop<128, 0>(acc, dum, sb, it, 8, wg, lane);
          if (tid == 0) sts32(sb + C_REQ + 24, ntask);
          float4* dst = g_acc + ((size_t)(blk * 8 + warp) * 80 + (ti % 5) * 16) * 32 + lane;
#pragma unroll
          for (int j = 0; j < 16; j++) red4(dst + j * 32, acc[j * 4], acc[j * 4 + 1], acc[j * 4 + 2], acc[j * 4 + 3]);
          signal(sb, nsig, CN_WO + blk, tid);
        } else if (type == T_F1) {
          float acc[32], dum[2];
          if (tid == 0) sts32(sb + C_REQ + 24, ntask);
          gemm_loop<64, 0>(acc, dum, sb, it, 5, wg, lane);
          ep_f1<4>(acc, blk * 128 + warp * 16, ti * 64, lane);
          signal(sb, nsig, CN_F1 + blk, tid);
        } else {
          float acc[32], dum[2];
          uint2 xv[8];
          float2 g[8];
#pragma unroll
          for (int j = 0; j < 8; j++) {
            xv[j] = __ldcg(g_x1f + ((size_t)(blk * 8 + warp) * 80 + ti * 8 + j) * 32 + lane);
            g[j] = __ldg(reinterpret_cast<const float2*>(g_mod + 5 * DM + ti * 64 + j * 8 + (lane & 3) * 2));
          }
          gemm_loop<64, 0>(acc, dum, sb, it, 12, wg, lane);
          if (tid == 0) sts32(sb + C_REQ + 24, ntask);
          const bool odd = lane & 1;
          uint2* dst = reinterpret_cast<uint2*>(out + (size_t)(blk * 128 + warp * 16 + (lane >> 2)) * DM + ti * 64 + (lane & 1) * 8 + (lane & 2) * 2);
#pragma unroll
          for (int j = 0; j < 8; j += 2) {
            uint32_t w[2][2];
#pragma unroll
            for (int e = 0; e < 2; e++) {
              const float* ap = &acc[(j + e) * 4];
              w[e][0] = pack_bf16(bf_lo(xv[j + e].x) + g[j + e].x * ap[0], bf_hi(xv[j + e].x) + g[j + e].y * ap[1]);
              w[e][1] = pack_bf16(bf_lo(xv[j + e].y) + g[j + e].x * ap[2], bf_hi(xv[j + e].y) + g[j + e].y * ap[3]);
            }
            dst[j * 2] = pair_x(w[0][0], w[1][0], odd);
            dst[j * 2 + 2 * DM] = pair_x(w[0][1], w[1][1], odd);
          }
        }
      } else if (type == T_Q || type == T_F1) {
        float acc[128], dum[2];
        gemm_loop<256, 0>(acc, dum, sb, it, 10, wg, lane);
        if (tid == 0) sts32(sb + C_REQ + 24, ntask);
        if (type == T_Q) {
          const int qb = idx / 24, nt = idx % 24;
          uint4* dst = reinterpret_cast<uint4*>(g_q) + ((size_t)(qb * 8 + warp) * 384 + nt * 16) * 32 + lane;
#pragma unroll
          for (int j = 0; j < 16; j++)
            dst[j * 32] = make_uint4(pack_bf16(acc[j * 8], acc[j * 8 + 1]), pack_bf16(acc[j * 8 + 2], acc[j * 8 + 3]),
                                     pack_bf16(acc[j * 8 + 4], acc[j * 8 + 5]), pack_bf16(acc[j * 8 + 6], acc[j * 8 + 7]));
          signal(sb, nsig, CN_Q + qb, tid);
        } else {
          ep_f1<16>(acc, blk * 128 + warp * 16, ti * 256, lane);
          signal(sb, nsig, CN_F1 + blk, tid);
        }
      } else if (type == T_WO || type == T_F2) {
        const int nh = ti & 1;
        float a0[96], a1[64];
        gemm_loop<192, 128>(a0, a1, sb, it, 24, wg, lane);
        if (tid == 0) sts32(sb + C_REQ + 24, ntask);
        const size_t fo = ((size_t)(blk * 8 + warp) * 80 + nh * 40) * 32 + lane;
        if (type == T_WO) {
          float4* dst = g_acc + fo;
#pragma unroll
          for (int j = 0; j < 24; j++) red4(dst + j * 32, a0[j * 4], a0[j * 4 + 1], a0[j * 4 + 2], a0[j * 4 + 3]);
#pragma unroll
          for (int j = 0; j < 16; j++) red4(dst + (24 + j) * 32, a1[j * 4], a1[j * 4 + 1], a1[j * 4 + 2], a1[j * 4 + 3]);
          signal(sb, nsig, CN_WO + blk, tid);
        } else {
          const bool odd = lane & 1;
          uint2* dst = reinterpret_cast<uint2*>(out + (size_t)(blk * 128 + warp * 16 + (lane >> 2)) * DM + nh * 320 + (lane & 1) * 8 + (lane & 2) * 2);
          const float2* gp = reinterpret_cast<const float2*>(g_mod + 5 * DM + nh * 320 + (lane & 3) * 2);
#pragma unroll
          for (int j4 = 0; j4 < 5; j4++) {
            uint2 xv[8];
#pragma unroll
            for (int j = 0; j < 8; j++) xv[j] = __ldcg(g_x1f + fo + (j4 * 8 + j) * 32);
#pragma unroll
            for (int j = 0; j < 8; j += 2) {
              uint32_t w[2][2];
#pragma unroll
              for (int e = 0; e < 2; e++) {
                const int t = j4 * 8 + j + e;
                const float* ap = t < 24 ? &a0[t * 4] : &a1[(t - 24) * 4];
                const float2 g = __ldg(gp + t * 4);
                w[e][0] = pack_bf16(bf_lo(xv[j + e].x) + g.x * ap[0], bf_hi(xv[j + e].x) + g.y * ap[1]);
                w[e][1] = pack_bf16(bf_lo(xv[j + e].y) + g.x * ap[2], bf_hi(xv[j + e].y) + g.y * ap[3]);
              }
              dst[(j4 * 8 + j) * 2] = pair_x(w[0][0], w[1][0], odd);
              dst[(j4 * 8 + j) * 2 + 2 * DM] = pair_x(w[0][1], w[1][1], odd);
            }
          }
        }
      } else if (type == T_ATT) {
        const int seg = idx >> 4, qh = warp & 1, dh = (warp >> 1) & 1, nu = blk >= TBA ? 2 : 4, h0 = (idx & 15) * nu;
        const int li = lane >> 3, lr = lane & 7;
#pragma unroll 1
        for (int u = 0; u < nu; u++, it++) {
          const uint32_t st = it & 3;
          if (u) mbar_wait_nt(sb + C_BAR + st * 8, (it >> 2) & 1);
          if (tid == 0 && u == nu - 2) sts32(sb + C_REQ + 24, ntask);
          if ((u & 1) == wg) {
            const int h = h0 + u;
            const uint32_t akx = sb + st * C_STAGE, avx = akx + 12288, akm = akx + 24576, avm = akx + 27648;
            float s[5][4];
#pragma unroll
            for (int n = 0; n < 5; n++)
#pragma unroll
              for (int j = 0; j < 4; j++) s[n][j] = 0.f;
            const int sw = (lr >> 1) & 3;
            const uint32_t kb0 = akx + ((li & 1) * 8 + lr) * 64 + (((li >> 1) ^ sw) * 16), kb1 = akx + ((li & 1) * 8 + lr) * 64 + (((2 + (li >> 1)) ^ sw) * 16);
#pragma unroll
            for (int k2 = 0; k2 < 6; k2++) {
              uint32_t bm[4];
              ldsm_x4_t(bm, akm + (k2 * 32 + lane) * 16);
#pragma unroll
              for (int e = 0; e < 2; e++) {
                const int ks = k2 * 2 + e;
                const uint4 qf = lds128(akx + 30720 + qh * 6144 + ks * 512 + lane * 16);
                const uint32_t a[4] = {qf.x, qf.y, qf.z, qf.w};
                uint32_t b[4];
                ldsm_x4_t(b, kb0 + ks * 1024);
                mma16816(s[0], a, b[0], b[1]);
                mma16816(s[1], a, b[2], b[3]);
                if (qh) {
                  ldsm_x4_t(b, kb1 + ks * 1024);
                  mma16816(s[2], a, b[0], b[1]);
                  mma16816(s[3], a, b[2], b[3]);
                }
                mma16816(s[4], a, bm[e * 2], bm[e * 2 + 1]);
              }
            }
            const float scale = 0.07216878364870322f * 1.4426950408889634f;
            uint32_t p[2][4], pm[2];
            float inv[2];
            {
              float mx[2] = {-INFINITY, -INFINITY};
#pragma unroll
              for (int n = 0; n < 5; n++)
#pragma unroll
                for (int j = 0; j < 4; j++) {
                  const int qi = qh * 16 + (lane >> 2) + (j >> 1) * 8, ki = n * 8 + (lane & 3) * 2 + (j & 1);
                  if (n < 4 && ki > qi) s[n][j] = -INFINITY;
                  mx[j >> 1] = fmaxf(mx[j >> 1], s[n][j]);
                }
              float sum[2] = {0.f, 0.f};
#pragma unroll
              for (int hh = 0; hh < 2; hh++) {
                mx[hh] = fmaxf(mx[hh], __shfl_xor_sync(0xffffffffu, mx[hh], 1));
                mx[hh] = fmaxf(mx[hh], __shfl_xor_sync(0xffffffffu, mx[hh], 2));
                mx[hh] *= -scale;
              }
#pragma unroll
              for (int n = 0; n < 5; n++)
#pragma unroll
                for (int j = 0; j < 4; j++) {
                  s[n][j] = ex2(fmaf(s[n][j], scale, mx[j >> 1]));
                  sum[j >> 1] += s[n][j];
                }
#pragma unroll
              for (int hh = 0; hh < 2; hh++) {
                sum[hh] += __shfl_xor_sync(0xffffffffu, sum[hh], 1);
                sum[hh] += __shfl_xor_sync(0xffffffffu, sum[hh], 2);
                inv[hh] = __frcp_rn(sum[hh]);
              }
#pragma unroll
              for (int kb = 0; kb < 2; kb++) {
                p[kb][0] = pack_bf16(s[2 * kb][0], s[2 * kb][1]);
                p[kb][1] = pack_bf16(s[2 * kb][2], s[2 * kb][3]);
                p[kb][2] = pack_bf16(s[2 * kb + 1][0], s[2 * kb + 1][1]);
                p[kb][3] = pack_bf16(s[2 * kb + 1][2], s[2 * kb + 1][3]);
              }
              pm[0] = pack_bf16(s[4][0], s[4][1]);
              pm[1] = pack_bf16(s[4][2], s[4][3]);
            }
            bf16* op = g_o + (size_t)(seg * SEG + qh * 16 + (lane >> 2)) * HD + h * DH + dh * 96 + (lane & 3) * 8;
#pragma unroll
            for (int g3 = 0; g3 < 3; g3++) {
              const int g32 = dh * 3 + g3;
              uint32_t bm[4], r0[4], r1[4];
              ldsm_x4(bm, avm + (g32 * 32 + lane) * 16);
#pragma unroll
              for (int j = 0; j < 4; j++) {
                float o[4] = {0.f, 0.f, 0.f, 0.f};
                uint32_t b[4];
                ldsm_x4(b, avx + (g32 * 32 + (lr >> 1) * 8 + j * 2 + (lr & 1)) * 64 + ((li ^ ((j + (lr >> 1)) & 3)) * 16));
                mma16816(o, p[0], b[0], b[1]);
                if (qh) mma16816(o, p[1], b[2], b[3]);
                mma1688(o, pm[0], pm[1], bm[j]);
                r0[j] = pack_bf16(o[0] * inv[0], o[1] * inv[0]);
                r1[j] = pack_bf16(o[2] * inv[1], o[3] * inv[1]);
              }
              *reinterpret_cast<uint4*>(op + g3 * 32) = make_uint4(r0[0], r0[1], r0[2], r0[3]);
              *reinterpret_cast<uint4*>(op + g3 * 32 + 8 * HD) = make_uint4(r1[0], r1[1], r1[2], r1[3]);
            }
          }
          __syncwarp();
          if (lane == 0) mbar_arrive(sb + C_BAR + 32 + st * 8);
        }
        signal(sb, nsig, CN_ATT + (seg >> 2), tid);
      } else {
        const uint32_t scr = sb + (it & 3) * C_STAGE, ebar = sb + C_BAR + 32 + (it & 3) * 8;
        if (lane == 0 && type != T_LN) mbar_arrive(ebar);
        it++;
        if (type == T_Z) {
          float4* d0 = g_acc + (size_t)idx * 20480 + tid;
#pragma unroll 4
          for (int i = 0; i < 80; i++) d0[i * 256] = make_float4(0.f, 0.f, 0.f, 0.f);
          signal(sb, nsig, CN_Z + idx, tid);
        } else {
          if ((idx >> 6) >= TBK) ln_task<1>(x, (idx >> 6) * 8 + (idx & 63), scr, ebar, warp, lane, sb + C_REQ + 24, ntask);
          else ln_task<2>(x, (idx >> 6) * 8 + (idx & 63) * 2, scr, ebar, warp, lane, sb + C_REQ + 24, ntask);
          signal(sb, nsig, CN_LN + (idx >> 6), tid);
        }
      }
      if (tid == 0) sts32(sb + C_REQ + 24, ntask);
    }
  }
  asm volatile("griddepcontrol.wait;" ::: "memory");
  TS(8);
}

typedef CUresult (*PFN_encodeTiled)(CUtensorMap*, CUtensorMapDataType, cuuint32_t, void*, const cuuint64_t*, const cuuint64_t*,
                                    const cuuint32_t*, const cuuint32_t*, CUtensorMapInterleave, CUtensorMapSwizzle,
                                    CUtensorMapL2promotion, CUtensorMapFloatOOBfill);
static PFN_encodeTiled g_encode = nullptr;

static CUtensorMap make_tm(const void* ptr, uint64_t cols, uint64_t rows, uint32_t bcols, uint32_t brows, CUtensorMapSwizzle swz) {
  CUtensorMap tm;
  cuuint64_t dims[2] = {cols, rows};
  cuuint64_t strides[1] = {cols * 2};
  cuuint32_t box[2] = {bcols, brows};
  cuuint32_t es[2] = {1, 1};
  g_encode(&tm, CU_TENSOR_MAP_DATA_TYPE_BFLOAT16, 2, const_cast<void*>(ptr), dims, strides, box, es, CU_TENSOR_MAP_INTERLEAVE_NONE, swz,
           CU_TENSOR_MAP_L2_PROMOTION_L2_256B, CU_TENSOR_MAP_FLOAT_OOB_FILL_NONE);
  return tm;
}
template <typename T>
static void* sym_addr(T& sym) {
  void* p = nullptr;
  cudaGetSymbolAddress(&p, sym);
  return p;
}

extern "C" void kernel_launch(void* const* d_in, const int* in_sizes, int n_in, void* d_out, int out_size) {
  const bf16* x = (const bf16*)d_in[0];
  const bf16* mem0 = (const bf16*)d_in[1];
  const bf16* Wq = (const bf16*)d_in[2];
  const bf16* Wk = (const bf16*)d_in[3];
  const bf16* Wv = (const bf16*)d_in[4];
  const bf16* Wo = (const bf16*)d_in[5];
  const bf16* w1 = (const bf16*)d_in[8];
  const bf16* w2 = (const bf16*)d_in[9];
  const bf16* c = (const bf16*)d_in[10];
  const bf16* wmod = (const bf16*)d_in[11];
  bf16* out = (bf16*)d_out;

  if (!g_encode) {
    cudaDriverEntryPointQueryResult qr;
    void* fn = nullptr;
    cudaGetDriverEntryPoint("cuTensorMapEncodeTiled", &fn, cudaEnableDefault, &qr);
    g_encode = (PFN_encodeTiled)fn;
    cudaFuncSetAttribute(k_cons, cudaFuncAttributeMaxDynamicSharedMemorySize, C_SMEM);
    cudaFuncSetAttribute(k_rec, cudaFuncAttributeMaxDynamicSharedMemorySize, R_SMEM);
  }
  bf16* p_h = (bf16*)sym_addr(g_h);
  bf16* p_o = (bf16*)sym_addr(g_o);
  bf16* p_h2 = (bf16*)sym_addr(g_h2);
  bf16* p_f = (bf16*)sym_addr(g_f);
  const CUtensorMapSwizzle S128 = CU_TENSOR_MAP_SWIZZLE_128B;

  CUtensorMap tA_h = make_tm(p_h, DM, S_TOK, 64, 128, S128);
  CUtensorMap tB_q = make_tm(Wq, HD, DM, 64, 64, S128);
  CUtensorMap tA_o = make_tm(p_o, HD, S_TOK, 64, 128, S128);
  CUtensorMap tB_o = make_tm(Wo, DM, HD, 64, 64, S128);
  CUtensorMap tA_h2 = make_tm(p_h2, DM, S_TOK, 64, 128, S128);
  CUtensorMap tB_w1 = make_tm(w1, FF, DM, 64, 64, S128);
  CUtensorMap tA_f = make_tm(p_f, FF, S_TOK, 64, 128, S128);
  CUtensorMap tB_w2 = make_tm(w2, DM, FF, 64, 64, S128);
  CUtensorMap tR_q = make_tm(Wq, HD, DM, 64, 160, S128);
  CUtensorMap tR_k = make_tm(Wk, HD, DM, 64, 160, S128);
  CUtensorMap tR_v = make_tm(Wv, HD, DM, 64, 160, S128);

  k_init<<<24, 640>>>(mem0, c, wmod);
  cudaLaunchConfig_t cfg = {};
  cudaLaunchAttribute at[1];
  at[0].id = cudaLaunchAttributeProgrammaticStreamSerialization;
  at[0].val.programmaticStreamSerializationAllowed = 1;
  cfg.attrs = at;
  cfg.numAttrs = 1;
  cfg.stream = cudaStreamPerThread;
  cfg.gridDim = dim3(96);
  cfg.blockDim = dim3(384);
  cfg.dynamicSmemBytes = R_SMEM;
  cudaLaunchKernelEx(&cfg, k_rec, tR_q, tR_k, tR_v, tB_o, x, Wv, Wo);
  cfg.gridDim = dim3(132);
  cfg.blockDim = dim3(384);
  cfg.dynamicSmemBytes = C_SMEM;
  at[0].val.programmaticStreamSerializationAllowed = 1;
  cfg.attrs = at;
  cfg.numAttrs = 1;
  cudaLaunchKernelEx(&cfg, k_cons, tA_h, tB_q, tA_o, tB_o, tA_h2, tB_w1, tA_f, tB_w2, x, out);
}
```
